```python
import torch

def _softmax(x, axis=-1):
    return torch.softmax(x, dim=axis)

def _gelu(x):
    return torch.nn.functional.gelu(x, approximate='tanh')

def _silu(x):
    return torch.nn.functional.silu(x)

def _sigmoid(x):
    return torch.sigmoid(x)

def _layernorm(x, axis=-1, eps=1e-05):
    m = x.mean(dim=axis, keepdim=True)
    v = x.var(dim=axis, keepdim=True, unbiased=False)
    return (x - m) / torch.sqrt(v + eps)

def _scatter_add(tgt, idx, src, axis=0):
    return tgt.clone().index_add_(axis, idx, src)

def _segment_sum(src, seg, n):
    out = torch.zeros((n,) + src.shape[1:], dtype=src.dtype)
    return out.index_add_(0, seg, src)

def _pad(x, pw):
    flat = tuple((v for pair in reversed(pw) for v in pair))
    return torch.nn.functional.pad(x, flat)
kernel_name = 'parallel_sum__sliding_local_dilated__mixer_gmlp__prompt'

def setup_inputs():

    _w = lambda a: (lambda t: t.to(torch.bfloat16) if t.is_floating_point() else t)(torch.as_tensor(a))

    def _A_setup():
        B, S, D = (1, 2048, 448)
        return {'x': _w((lambda *s: torch.randn(*s, dtype=torch.bfloat16) * 0.05)(B, S, D)), 'wqkv': _w((lambda *s: torch.randn(*s, dtype=torch.bfloat16) * 0.1)(D, 3 * D)), 'wo': _w((lambda *s: torch.randn(*s, dtype=torch.bfloat16) * 0.05)(D, D))}
    _A_in = _A_setup()

    def _B_setup():
        B, S, D, F = (1, 2048, 448, 1792)
        Fh = F // 2
        return {'x': _w((lambda *s: torch.randn(*s, dtype=torch.bfloat16) * 0.05)(B, S, D)), 'w_in': _w((lambda *s: torch.randn(*s, dtype=torch.bfloat16) * 0.4)(D, 2 * Fh)), 'w_sp': _w(0.01 * (lambda *s: torch.randn(*s, dtype=torch.bfloat16) * 0.4)(S, S)), 'b_sp': _w(1.0 + 0.01 * (lambda *s: torch.randn(*s, dtype=torch.bfloat16) * 0.05)(S)), 'w_out': _w((lambda *s: torch.randn(*s, dtype=torch.bfloat16) * 0.05)(Fh, D))}
    _B_in = _B_setup()
    return {'A_x': _A_in['x'], 'A_wqkv': _A_in['wqkv'], 'A_wo': _A_in['wo'], 'B_x': _B_in['x'], 'B_w_in': _B_in['w_in'], 'B_w_sp': _B_in['w_sp'], 'B_b_sp': _B_in['b_sp'], 'B_w_out': _B_in['w_out']}

def reference(A_x, A_wqkv, A_wo, B_x, B_w_in, B_w_sp, B_b_sp, B_w_out):

    def _A_ref(x, wqkv, wo):
        B, S, D = x.shape
        H = 16
        Dh = D // H
        W, dil = (8, 2)
        qkv = (lambda x, *d: x.permute(*d))((x @ wqkv).reshape(B, S, 3, H, Dh), 2, 0, 3, 1, 4)
        q, k, v = (qkv[0], qkv[1], qkv[2])
        scale = Dh ** (-0.5)
        pos = torch.arange(S)
        off = torch.arange(W) * dil
        idx = pos[:, None] - off[None, :]
        mask = idx >= 0
        idx_c = torch.where(mask, idx, 0).reshape(-1)
        kg = k[:, :, idx_c, :].reshape(B, H, S, W, Dh)
        vg = v[:, :, idx_c, :].reshape(B, H, S, W, Dh)
        logits = torch.einsum('bhsd,bhswd->bhsw', q, kg) * scale
        logits = torch.where(mask[None, None, :, :], logits, -1000000000.0)
        attn = _softmax(logits, axis=-1)
        o = torch.einsum('bhsw,bhswd->bhsd', attn, vg)
        return (lambda x, *d: x.permute(*d))(o, 0, 2, 1, 3).reshape(B, S, D) @ wo

    def _B_ref(x, w_in, w_sp, b_sp, w_out):
        B, S, D = x.shape
        F = w_in.shape[-1]
        Fh = F // 2
        z = _gelu(torch.einsum('bsd,df->bsf', x, w_in))
        z1 = z[..., :Fh].clone()
        z2 = _layernorm(z[..., Fh:], axis=-1)
        g = torch.einsum('ts,bsf->btf', w_sp, z2) + b_sp[None, :, None]
        return torch.einsum('bsf,fd->bsd', z1 * g, w_out)
    x = A_x
    xn = _layernorm(x, axis=-1)
    return x + _A_ref(xn, A_wqkv, A_wo) + _B_ref(xn, B_w_in, B_w_sp, B_b_sp, B_w_out)
```

```cpp
#include <cuda_runtime.h>
#include <cuda_bf16.h>
#include <cuda.h>
#include <stdint.h>

namespace {

typedef __nv_bfloat16 bf16;

__device__ __align__(1024) uint8_t g_z2t[16 * 8 * 28672];
__device__ __align__(1024) uint8_t g_ou[16 * 2 * 168 * 1024];
__device__ __align__(1024) uint8_t g_qkv[168 * 2 * 1024 * 16];
__device__ __align__(128) uint4 g_stats[16 * 8 * 64];
__device__ __align__(128) unsigned g_z2flag[8 * 32];
__device__ __align__(128) unsigned g_qflag[32 * 8];
__device__ __align__(128) unsigned g_ouflag[32 * 16];
__device__ unsigned g_done;
#define TS(k) do {} while (0)
#define SPIN_CHECK(n, code) if (++n > (1u << 20)) __trap();

constexpr uint32_t XN_OFF = 0;
constexpr uint32_t RINGA_OFF = 114688;
constexpr uint32_t Z2S_OFF = 196608;
constexpr uint32_t GSTRIDE = 30720;
constexpr uint32_t GRAN = 14336;
constexpr uint32_t BAR_OFF = 225280;
constexpr int B_FULLA = 0, B_DONEA = 21, B_FULLB = 42, B_DONEB = 74, B_FULLCW = 106, B_FULLCA = 118,
              B_DONEC = 142, B_Z2SFREE = 154, B_USTFREE = 155, NBARS = 156;
constexpr uint32_t SMEM_BYTES = BAR_OFF + NBARS * 8 + 1024;
constexpr uint32_t GORDER = 0x4365210u;

__device__ __forceinline__ uint32_t smem_u32(const void* p) { return (uint32_t)__cvta_generic_to_shared(p); }
__device__ __forceinline__ void mbar_init(uint32_t bar, uint32_t count) {
    asm volatile("mbarrier.init.shared::cta.b64 [%0], %1;" ::"r"(bar), "r"(count) : "memory");
}
__device__ __forceinline__ void mbar_expect_tx(uint32_t bar, uint32_t bytes) {
    asm volatile("mbarrier.arrive.expect_tx.shared::cta.b64 _, [%0], %1;" ::"r"(bar), "r"(bytes) : "memory");
}
__device__ __forceinline__ void mbar_arrive(uint32_t bar) {
    asm volatile("mbarrier.arrive.shared::cta.b64 _, [%0];" ::"r"(bar) : "memory");
}
__device__ __forceinline__ void mbar_arrive_remote(uint32_t bar, uint32_t cta) {
    asm volatile("{\n.reg .b32 ra;\nmapa.shared::cluster.u32 ra, %0, %1;\nmbarrier.arrive.shared::cluster.b64 _, [ra];\n}\n" ::"r"(bar), "r"(cta) : "memory");
}
__device__ __forceinline__ bool mbar_try(uint32_t bar) {
    uint32_t ok;
    asm volatile("{\n.reg .pred p;\nmbarrier.try_wait.parity.shared::cta.b64 p, [%1], 0;\nselp.u32 %0, 1, 0, p;\n}\n" : "=r"(ok) : "r"(bar) : "memory");
    return ok != 0;
}
__device__ __forceinline__ void mbar_wait(uint32_t bar) {
    if (mbar_try(bar)) return;
    uint32_t n = 0;
    while (!mbar_try(bar)) { SPIN_CHECK(n, ((bar & 0x7ff) >> 3)) }
}
__device__ __forceinline__ void tma_3d(uint32_t dst, const CUtensorMap* tm, int c0, int c1, int c2, uint32_t bar) {
    asm volatile("cp.async.bulk.tensor.3d.shared::cluster.global.mbarrier::complete_tx::bytes [%0], [%1, {%3, %4, %5}], [%2];"
                 ::"r"(dst), "l"(tm), "r"(bar), "r"(c0), "r"(c1), "r"(c2) : "memory");
}
__device__ __forceinline__ void tma_2d_mc(uint32_t dst, const CUtensorMap* tm, int c0, int c1, uint32_t bar) {
    asm volatile("cp.async.bulk.tensor.2d.shared::cluster.global.mbarrier::complete_tx::bytes.multicast::cluster [%0], [%1, {%3, %4}], [%2], %5;"
                 ::"r"(dst), "l"(tm), "r"(bar), "r"(c0), "r"(c1), "h"((uint16_t)3) : "memory");
}
__device__ __forceinline__ void bulk_load(uint32_t dst, const void* src, uint32_t bytes, uint32_t bar) {
    asm volatile("cp.async.bulk.shared::cluster.global.mbarrier::complete_tx::bytes [%0], [%1], %2, [%3];"
                 ::"r"(dst), "l"(src), "r"(bytes), "r"(bar) : "memory");
}
__device__ __forceinline__ void bulk_load_mc(uint32_t dst, const void* src, uint32_t bytes, uint32_t bar) {
    asm volatile("cp.async.bulk.shared::cluster.global.mbarrier::complete_tx::bytes.multicast::cluster [%0], [%1], %2, [%3], %4;"
                 ::"r"(dst), "l"(src), "r"(bytes), "r"(bar), "h"((uint16_t)3) : "memory");
}
__device__ __forceinline__ void bulk_store(void* dst, uint32_t src, uint32_t bytes) {
    asm volatile("cp.async.bulk.global.shared::cta.bulk_group [%0], [%1], %2;" ::"l"(dst), "r"(src), "r"(bytes) : "memory");
    asm volatile("cp.async.bulk.commit_group;" ::: "memory");
}
__device__ __forceinline__ void l2_prefetch(const void* p, uint32_t bytes) {
    asm volatile("cp.async.bulk.prefetch.L2.global [%0], %1;" ::"l"(p), "r"(bytes) : "memory");
}
__device__ __forceinline__ void wgmma_fence() { asm volatile("wgmma.fence.sync.aligned;" ::: "memory"); }
__device__ __forceinline__ void wgmma_commit() { asm volatile("wgmma.commit_group.sync.aligned;" ::: "memory"); }
template <int N> __device__ __forceinline__ void wgmma_wait() { asm volatile("wgmma.wait_group.sync.aligned %0;" ::"n"(N) : "memory"); }
template <int N> __device__ __forceinline__ void reg_fence(float (&d)[N]) {
#pragma unroll
    for (int k = 0; k < N; k++) asm volatile("" : "+f"(d[k])::"memory");
}
__device__ __forceinline__ uint64_t mk_desc(uint32_t addr, uint32_t lbo, uint32_t sbo, uint32_t mode) {
    return (uint64_t)((addr & 0x3FFFF) >> 4) | ((uint64_t)(lbo >> 4) << 16) | ((uint64_t)(sbo >> 4) << 32) | ((uint64_t)mode << 62);
}
__device__ __forceinline__ void bar_sync(int id, int n) { asm volatile("bar.sync %0, %1;" ::"r"(id), "r"(n) : "memory"); }
__device__ __forceinline__ void bar_arrive(int id, int n) { asm volatile("bar.arrive %0, %1;" ::"r"(id), "r"(n) : "memory"); }
__device__ __forceinline__ void fence_async_smem() { asm volatile("fence.proxy.async.shared::cta;" ::: "memory"); }
__device__ __forceinline__ void fence_async_global() { asm volatile("fence.proxy.async.global;" ::: "memory"); }
__device__ __forceinline__ void cluster_arrive() { asm volatile("barrier.cluster.arrive.release.aligned;" ::: "memory"); }
__device__ __forceinline__ void cluster_wait() { asm volatile("barrier.cluster.wait.acquire.aligned;" ::: "memory"); }
__device__ __forceinline__ unsigned ld_acquire(const unsigned* p) {
    unsigned v; asm volatile("ld.acquire.gpu.global.u32 %0, [%1];" : "=r"(v) : "l"(p) : "memory"); return v;
}
__device__ __forceinline__ void st_release(unsigned* p, unsigned v) {
    asm volatile("st.release.gpu.global.u32 [%0], %1;" ::"l"(p), "r"(v) : "memory");
}
__device__ __forceinline__ uint4 ld_relaxed_v4(const uint4* p) {
    uint4 v; asm volatile("ld.relaxed.gpu.global.v4.u32 {%0,%1,%2,%3}, [%4];" : "=r"(v.x), "=r"(v.y), "=r"(v.z), "=r"(v.w) : "l"(p) : "memory"); return v;
}
__device__ __forceinline__ void st_relaxed_v4(uint4* p, uint4 v) {
    asm volatile("st.relaxed.gpu.global.v4.u32 [%0], {%1,%2,%3,%4};" ::"l"(p), "r"(v.x), "r"(v.y), "r"(v.z), "r"(v.w) : "memory");
}
__device__ __forceinline__ uint4 ld_nc_v4(const void* p) {
    uint4 v; asm volatile("ld.global.nc.L1::no_allocate.v4.u32 {%0,%1,%2,%3}, [%4];" : "=r"(v.x), "=r"(v.y), "=r"(v.z), "=r"(v.w) : "l"(p)); return v;
}
__device__ __forceinline__ uint4 ld_v4(const void* p) {
    uint4 v; asm volatile("ld.global.v4.u32 {%0,%1,%2,%3}, [%4];" : "=r"(v.x), "=r"(v.y), "=r"(v.z), "=r"(v.w) : "l"(p) : "memory"); return v;
}
__device__ __forceinline__ void sts_v4(uint32_t a, uint4 v) {
    asm volatile("st.shared.v4.u32 [%0], {%1,%2,%3,%4};" ::"r"(a), "r"(v.x), "r"(v.y), "r"(v.z), "r"(v.w) : "memory");
}
__device__ __forceinline__ uint32_t pack_bf16(float lo, float hi) {
    uint32_t r; asm("cvt.rn.bf16x2.f32 %0, %1, %2;" : "=r"(r) : "f"(hi), "f"(lo)); return r;
}
__device__ __forceinline__ float bf_lo(uint32_t r) { return __uint_as_float(r << 16); }
__device__ __forceinline__ float bf_hi(uint32_t r) { return __uint_as_float(r & 0xffff0000u); }
__device__ __forceinline__ uint32_t sub_bf16x2(uint32_t a, uint32_t b) {
    uint32_t r; asm("sub.rn.bf16x2 %0, %1, %2;" : "=r"(r) : "r"(a), "r"(b)); return r;
}
__device__ __forceinline__ void mma16816(float (&c)[4], uint32_t a0, uint32_t a1, uint32_t a2, uint32_t a3, uint32_t b0, uint32_t b1) {
    asm("mma.sync.aligned.m16n8k16.row.col.f32.bf16.bf16.f32 {%0,%1,%2,%3}, {%4,%5,%6,%7}, {%8,%9}, {%0,%1,%2,%3};"
        : "+f"(c[0]), "+f"(c[1]), "+f"(c[2]), "+f"(c[3]) : "r"(a0), "r"(a1), "r"(a2), "r"(a3), "r"(b0), "r"(b1));
}
__device__ __forceinline__ void mma1688(float (&c)[4], uint32_t a0, uint32_t a1, uint32_t b0) {
    asm("mma.sync.aligned.m16n8k8.row.col.f32.bf16.bf16.f32 {%0,%1,%2,%3}, {%4,%5}, {%6}, {%0,%1,%2,%3};"
        : "+f"(c[0]), "+f"(c[1]), "+f"(c[2]), "+f"(c[3]) : "r"(a0), "r"(a1), "r"(b0));
}
__device__ __forceinline__ uint32_t movmat(uint32_t a) {
    uint32_t d; asm("movmatrix.sync.aligned.m8n8.trans.b16 %0, %1;" : "=r"(d) : "r"(a)); return d;
}
__device__ __forceinline__ void stmat_x4(uint32_t a, uint32_t r0, uint32_t r1, uint32_t r2, uint32_t r3) {
    asm volatile("stmatrix.sync.aligned.m8n8.x4.shared.b16 [%0], {%1,%2,%3,%4};" ::"r"(a), "r"(r0), "r"(r1), "r"(r2), "r"(r3) : "memory");
}
__device__ __forceinline__ void stmat_x4_t(uint32_t a, uint32_t r0, uint32_t r1, uint32_t r2, uint32_t r3) {
    asm volatile("stmatrix.sync.aligned.m8n8.x4.trans.shared.b16 [%0], {%1,%2,%3,%4};" ::"r"(a), "r"(r0), "r"(r1), "r"(r2), "r"(r3) : "memory");
}
__device__ __forceinline__ float gelu_tanh(float y) {
    float p = fmaf(y * y, 0.035677408136f, 0.797884560803f);
    float th; asm("tanh.approx.f32 %0, %1;" : "=f"(th) : "f"(y * p));
    float h = 0.5f * y;
    return fmaf(h, th, h);
}
__device__ __forceinline__ float ex2(float x) { float r; asm("ex2.approx.ftz.f32 %0, %1;" : "=f"(r) : "f"(x)); return r; }

template <int TB>
__device__ __forceinline__ void wgmma_n56(float (&d)[28], uint64_t da, uint64_t db, bool acc) {
    if (acc) {
        asm volatile("wgmma.mma_async.sync.aligned.m64n56k16.f32.bf16.bf16 {%0, %1, %2, %3, %4, %5, %6, %7, %8, %9, %10, %11, %12, %13, %14, %15, %16, %17, %18, %19, %20, %21, %22, %23, %24, %25, %26, %27}, %28, %29, 1, 1, 1, 0, %30;\n"
            : "+f"(d[0]), "+f"(d[1]), "+f"(d[2]), "+f"(d[3]), "+f"(d[4]), "+f"(d[5]), "+f"(d[6]), "+f"(d[7]), "+f"(d[8]), "+f"(d[9]), "+f"(d[10]), "+f"(d[11]), "+f"(d[12]), "+f"(d[13]), "+f"(d[14]), "+f"(d[15]), "+f"(d[16]), "+f"(d[17]), "+f"(d[18]), "+f"(d[19]), "+f"(d[20]), "+f"(d[21]), "+f"(d[22]), "+f"(d[23]), "+f"(d[24]), "+f"(d[25]), "+f"(d[26]), "+f"(d[27])
            : "l"(da), "l"(db), "n"(TB));
    } else {
        asm volatile("wgmma.mma_async.sync.aligned.m64n56k16.f32.bf16.bf16 {%0, %1, %2, %3, %4, %5, %6, %7, %8, %9, %10, %11, %12, %13, %14, %15, %16, %17, %18, %19, %20, %21, %22, %23, %24, %25, %26, %27}, %28, %29, 0, 1, 1, 0, %30;\n"
            : "=f"(d[0]), "=f"(d[1]), "=f"(d[2]), "=f"(d[3]), "=f"(d[4]), "=f"(d[5]), "=f"(d[6]), "=f"(d[7]), "=f"(d[8]), "=f"(d[9]), "=f"(d[10]), "=f"(d[11]), "=f"(d[12]), "=f"(d[13]), "=f"(d[14]), "=f"(d[15]), "=f"(d[16]), "=f"(d[17]), "=f"(d[18]), "=f"(d[19]), "=f"(d[20]), "=f"(d[21]), "=f"(d[22]), "=f"(d[23]), "=f"(d[24]), "=f"(d[25]), "=f"(d[26]), "=f"(d[27])
            : "l"(da), "l"(db), "n"(TB));
    }
}
template <int TB>
__device__ __forceinline__ void wgmma_n112(float (&d)[56], uint64_t da, uint64_t db, bool acc) {
    if (acc) {
        asm volatile("wgmma.mma_async.sync.aligned.m64n112k16.f32.bf16.bf16 {%0, %1, %2, %3, %4, %5, %6, %7, %8, %9, %10, %11, %12, %13, %14, %15, %16, %17, %18, %19, %20, %21, %22, %23, %24, %25, %26, %27, %28, %29, %30, %31, %32, %33, %34, %35, %36, %37, %38, %39, %40, %41, %42, %43, %44, %45, %46, %47, %48, %49, %50, %51, %52, %53, %54, %55}, %56, %57, 1, 1, 1, 0, %58;\n"
            : "+f"(d[0]), "+f"(d[1]), "+f"(d[2]), "+f"(d[3]), "+f"(d[4]), "+f"(d[5]), "+f"(d[6]), "+f"(d[7]), "+f"(d[8]), "+f"(d[9]), "+f"(d[10]), "+f"(d[11]), "+f"(d[12]), "+f"(d[13]), "+f"(d[14]), "+f"(d[15]), "+f"(d[16]), "+f"(d[17]), "+f"(d[18]), "+f"(d[19]), "+f"(d[20]), "+f"(d[21]), "+f"(d[22]), "+f"(d[23]), "+f"(d[24]), "+f"(d[25]), "+f"(d[26]), "+f"(d[27]), "+f"(d[28]), "+f"(d[29]), "+f"(d[30]), "+f"(d[31]), "+f"(d[32]), "+f"(d[33]), "+f"(d[34]), "+f"(d[35]), "+f"(d[36]), "+f"(d[37]), "+f"(d[38]), "+f"(d[39]), "+f"(d[40]), "+f"(d[41]), "+f"(d[42]), "+f"(d[43]), "+f"(d[44]), "+f"(d[45]), "+f"(d[46]), "+f"(d[47]), "+f"(d[48]), "+f"(d[49]), "+f"(d[50]), "+f"(d[51]), "+f"(d[52]), "+f"(d[53]), "+f"(d[54]), "+f"(d[55])
            : "l"(da), "l"(db), "n"(TB));
    } else {
        asm volatile("wgmma.mma_async.sync.aligned.m64n112k16.f32.bf16.bf16 {%0, %1, %2, %3, %4, %5, %6, %7, %8, %9, %10, %11, %12, %13, %14, %15, %16, %17, %18, %19, %20, %21, %22, %23, %24, %25, %26, %27, %28, %29, %30, %31, %32, %33, %34, %35, %36, %37, %38, %39, %40, %41, %42, %43, %44, %45, %46, %47, %48, %49, %50, %51, %52, %53, %54, %55}, %56, %57, 0, 1, 1, 0, %58;\n"
            : "=f"(d[0]), "=f"(d[1]), "=f"(d[2]), "=f"(d[3]), "=f"(d[4]), "=f"(d[5]), "=f"(d[6]), "=f"(d[7]), "=f"(d[8]), "=f"(d[9]), "=f"(d[10]), "=f"(d[11]), "=f"(d[12]), "=f"(d[13]), "=f"(d[14]), "=f"(d[15]), "=f"(d[16]), "=f"(d[17]), "=f"(d[18]), "=f"(d[19]), "=f"(d[20]), "=f"(d[21]), "=f"(d[22]), "=f"(d[23]), "=f"(d[24]), "=f"(d[25]), "=f"(d[26]), "=f"(d[27]), "=f"(d[28]), "=f"(d[29]), "=f"(d[30]), "=f"(d[31]), "=f"(d[32]), "=f"(d[33]), "=f"(d[34]), "=f"(d[35]), "=f"(d[36]), "=f"(d[37]), "=f"(d[38]), "=f"(d[39]), "=f"(d[40]), "=f"(d[41]), "=f"(d[42]), "=f"(d[43]), "=f"(d[44]), "=f"(d[45]), "=f"(d[46]), "=f"(d[47]), "=f"(d[48]), "=f"(d[49]), "=f"(d[50]), "=f"(d[51]), "=f"(d[52]), "=f"(d[53]), "=f"(d[54]), "=f"(d[55])
            : "l"(da), "l"(db), "n"(TB));
    }
}
template <int TB>
__device__ __forceinline__ void wgmma_n168(float (&d)[84], uint64_t da, uint64_t db, bool acc) {
    if (acc) {
        asm volatile("wgmma.mma_async.sync.aligned.m64n168k16.f32.bf16.bf16 {%0, %1, %2, %3, %4, %5, %6, %7, %8, %9, %10, %11, %12, %13, %14, %15, %16, %17, %18, %19, %20, %21, %22, %23, %24, %25, %26, %27, %28, %29, %30, %31, %32, %33, %34, %35, %36, %37, %38, %39, %40, %41, %42, %43, %44, %45, %46, %47, %48, %49, %50, %51, %52, %53, %54, %55, %56, %57, %58, %59, %60, %61, %62, %63, %64, %65, %66, %67, %68, %69, %70, %71, %72, %73, %74, %75, %76, %77, %78, %79, %80, %81, %82, %83}, %84, %85, 1, 1, 1, 0, %86;\n"
            : "+f"(d[0]), "+f"(d[1]), "+f"(d[2]), "+f"(d[3]), "+f"(d[4]), "+f"(d[5]), "+f"(d[6]), "+f"(d[7]), "+f"(d[8]), "+f"(d[9]), "+f"(d[10]), "+f"(d[11]), "+f"(d[12]), "+f"(d[13]), "+f"(d[14]), "+f"(d[15]), "+f"(d[16]), "+f"(d[17]), "+f"(d[18]), "+f"(d[19]), "+f"(d[20]), "+f"(d[21]), "+f"(d[22]), "+f"(d[23]), "+f"(d[24]), "+f"(d[25]), "+f"(d[26]), "+f"(d[27]), "+f"(d[28]), "+f"(d[29]), "+f"(d[30]), "+f"(d[31]), "+f"(d[32]), "+f"(d[33]), "+f"(d[34]), "+f"(d[35]), "+f"(d[36]), "+f"(d[37]), "+f"(d[38]), "+f"(d[39]), "+f"(d[40]), "+f"(d[41]), "+f"(d[42]), "+f"(d[43]), "+f"(d[44]), "+f"(d[45]), "+f"(d[46]), "+f"(d[47]), "+f"(d[48]), "+f"(d[49]), "+f"(d[50]), "+f"(d[51]), "+f"(d[52]), "+f"(d[53]), "+f"(d[54]), "+f"(d[55]), "+f"(d[56]), "+f"(d[57]), "+f"(d[58]), "+f"(d[59]), "+f"(d[60]), "+f"(d[61]), "+f"(d[62]), "+f"(d[63]), "+f"(d[64]), "+f"(d[65]), "+f"(d[66]), "+f"(d[67]), "+f"(d[68]), "+f"(d[69]), "+f"(d[70]), "+f"(d[71]), "+f"(d[72]), "+f"(d[73]), "+f"(d[74]), "+f"(d[75]), "+f"(d[76]), "+f"(d[77]), "+f"(d[78]), "+f"(d[79]), "+f"(d[80]), "+f"(d[81]), "+f"(d[82]), "+f"(d[83])
            : "l"(da), "l"(db), "n"(TB));
    } else {
        asm volatile("wgmma.mma_async.sync.aligned.m64n168k16.f32.bf16.bf16 {%0, %1, %2, %3, %4, %5, %6, %7, %8, %9, %10, %11, %12, %13, %14, %15, %16, %17, %18, %19, %20, %21, %22, %23, %24, %25, %26, %27, %28, %29, %30, %31, %32, %33, %34, %35, %36, %37, %38, %39, %40, %41, %42, %43, %44, %45, %46, %47, %48, %49, %50, %51, %52, %53, %54, %55, %56, %57, %58, %59, %60, %61, %62, %63, %64, %65, %66, %67, %68, %69, %70, %71, %72, %73, %74, %75, %76, %77, %78, %79, %80, %81, %82, %83}, %84, %85, 0, 1, 1, 0, %86;\n"
            : "=f"(d[0]), "=f"(d[1]), "=f"(d[2]), "=f"(d[3]), "=f"(d[4]), "=f"(d[5]), "=f"(d[6]), "=f"(d[7]), "=f"(d[8]), "=f"(d[9]), "=f"(d[10]), "=f"(d[11]), "=f"(d[12]), "=f"(d[13]), "=f"(d[14]), "=f"(d[15]), "=f"(d[16]), "=f"(d[17]), "=f"(d[18]), "=f"(d[19]), "=f"(d[20]), "=f"(d[21]), "=f"(d[22]), "=f"(d[23]), "=f"(d[24]), "=f"(d[25]), "=f"(d[26]), "=f"(d[27]), "=f"(d[28]), "=f"(d[29]), "=f"(d[30]), "=f"(d[31]), "=f"(d[32]), "=f"(d[33]), "=f"(d[34]), "=f"(d[35]), "=f"(d[36]), "=f"(d[37]), "=f"(d[38]), "=f"(d[39]), "=f"(d[40]), "=f"(d[41]), "=f"(d[42]), "=f"(d[43]), "=f"(d[44]), "=f"(d[45]), "=f"(d[46]), "=f"(d[47]), "=f"(d[48]), "=f"(d[49]), "=f"(d[50]), "=f"(d[51]), "=f"(d[52]), "=f"(d[53]), "=f"(d[54]), "=f"(d[55]), "=f"(d[56]), "=f"(d[57]), "=f"(d[58]), "=f"(d[59]), "=f"(d[60]), "=f"(d[61]), "=f"(d[62]), "=f"(d[63]), "=f"(d[64]), "=f"(d[65]), "=f"(d[66]), "=f"(d[67]), "=f"(d[68]), "=f"(d[69]), "=f"(d[70]), "=f"(d[71]), "=f"(d[72]), "=f"(d[73]), "=f"(d[74]), "=f"(d[75]), "=f"(d[76]), "=f"(d[77]), "=f"(d[78]), "=f"(d[79]), "=f"(d[80]), "=f"(d[81]), "=f"(d[82]), "=f"(d[83])
            : "l"(da), "l"(db), "n"(TB));
    }
}

struct Params {
    CUtensorMap tm_win;
    CUtensorMap tm_wqkv;
    CUtensorMap tm_wsp;
    CUtensorMap tm_wo;
    CUtensorMap tm_wout;
    const bf16* x;
    const bf16* wqkv;
    const bf16* wo;
    const bf16* win;
    const bf16* wsp;
    const bf16* bsp;
    const bf16* wout;
    bf16* out;
};

__device__ __forceinline__ uint32_t greg(int pos) { return ((GORDER >> (4 * pos)) & 7u) * GSTRIDE; }

__global__ void __cluster_dims__(2, 1, 1) __launch_bounds__(384, 1)
fused_kernel(const __grid_constant__ Params P) {
    extern __shared__ __align__(1024) uint8_t smem_raw[];
    const uint32_t sb = (smem_u32(smem_raw) + 1023u) & ~1023u;
    const uint32_t bars = sb + BAR_OFF;
    const int h = blockIdx.x & 1;
    const int pr = blockIdx.x >> 1;
    const int i = pr & 15, jj = pr >> 4, j = 2 * jj + h;
    const int lane = threadIdx.x & 31, g = lane >> 2, t = lane & 3;
    const int warp = threadIdx.x >> 5;
    unsigned epoch;
    asm volatile("ld.relaxed.gpu.global.u32 %0, [%1];" : "=r"(epoch) : "l"(&g_done) : "memory");

    if (warp < 8) {
        const int wg = warp >> 2, w = warp & 3;
        const bool sig = (threadIdx.x & 127) == 0;
        const bool sigr = (threadIdx.x & 127) == 32;
        uint4 xa[14], xb[14];
        const int pg = (g >> 1) | ((g & 1) << 2);
        {
            const uint4* xp = reinterpret_cast<const uint4*>(P.x + (size_t)(i * 128 + warp * 16 + pg) * 448) + t;
#pragma unroll
            for (int c = 0; c < 14; c++) { xa[c] = ld_nc_v4(xp + 4 * c); xb[c] = ld_nc_v4(xp + 4 * c + 8 * 56); }
        }
        cluster_arrive();
        asm volatile("setmaxnreg.inc.sync.aligned.u32 208;");
        float dma, dmb;
        {
            float sA[4] = {0.f, 0.f, 0.f, 0.f}, sB[4] = {0.f, 0.f, 0.f, 0.f};
            const uint32_t ONES = 0x3F803F80u;
#pragma unroll
            for (int c = 0; c < 14; c++) {
                mma16816(sA, xa[c].x, xb[c].x, xa[c].y, xb[c].y, ONES, ONES);
                mma16816(sB, xa[c].z, xb[c].z, xa[c].w, xb[c].w, ONES, ONES);
            }
            const float ma = (sA[0] + sB[0]) * (1.0f / 448.0f), mb = (sA[2] + sB[2]) * (1.0f / 448.0f);
            const uint32_t ma2 = pack_bf16(ma, ma), mb2 = pack_bf16(mb, mb);
            dma = ma - bf_lo(ma2); dmb = mb - bf_lo(mb2);
            const uint32_t rowaddr = sb + XN_OFF + (warp * 16 + pg) * 128;
#pragma unroll
            for (int c = 0; c < 14; c++) {
                xa[c].x = sub_bf16x2(xa[c].x, ma2); xa[c].y = sub_bf16x2(xa[c].y, ma2);
                xa[c].z = sub_bf16x2(xa[c].z, ma2); xa[c].w = sub_bf16x2(xa[c].w, ma2);
                xb[c].x = sub_bf16x2(xb[c].x, mb2); xb[c].y = sub_bf16x2(xb[c].y, mb2);
                xb[c].z = sub_bf16x2(xb[c].z, mb2); xb[c].w = sub_bf16x2(xb[c].w, mb2);
                const uint32_t a = rowaddr + (c >> 1) * 16384 + (((((c & 1) << 2) | t) ^ pg) << 4);
                sts_v4(a, xa[c]);
                sts_v4(a + 1024, xb[c]);
            }
        }
        fence_async_smem();
        bar_sync(1 + wg, 128);
        cluster_wait();
        if (threadIdx.x == 0) TS(0);

        const uint64_t dA_xn = mk_desc(sb + XN_OFF + wg * 8192, 16, 1024, 1);
        const uint64_t dB_ra = mk_desc(sb + RINGA_OFF, 8192, 1024, 1);
        float acc_a[56], acc_b[56], acc_c[84];
        float rs0, rs1;
        {
            float qa = 0.f, qb = 0.f, qa2 = 0.f, qb2 = 0.f;
#pragma unroll
            for (int kb = 0; kb < 7; kb++) {
                mbar_wait(bars + 8 * (B_FULLA + kb));
                wgmma_fence();
#pragma unroll
                for (int k = 0; k < 4; k++)
                    wgmma_n112<1>(acc_a, dA_xn + ((kb * 16384 + k * 32) >> 4), dB_ra + ((((kb + 1) % 5) * 16384 + k * 2048) >> 4), (kb | k) != 0);
                wgmma_commit();
                if (kb > 0) { wgmma_wait<1>(); if (sig) mbar_arrive(bars + 8 * (B_DONEA + kb - 1)); }
#pragma unroll
                for (int c = 2 * kb; c < 2 * kb + 2; c++) {
                    float v;
                    v = bf_lo(xa[c].x); qa = fmaf(v, v, qa); v = bf_hi(xa[c].x); qa2 = fmaf(v, v, qa2);
                    v = bf_lo(xa[c].y); qa = fmaf(v, v, qa); v = bf_hi(xa[c].y); qa2 = fmaf(v, v, qa2);
                    v = bf_lo(xa[c].z); qa = fmaf(v, v, qa); v = bf_hi(xa[c].z); qa2 = fmaf(v, v, qa2);
                    v = bf_lo(xa[c].w); qa = fmaf(v, v, qa); v = bf_hi(xa[c].w); qa2 = fmaf(v, v, qa2);
                    v = bf_lo(xb[c].x); qb = fmaf(v, v, qb); v = bf_hi(xb[c].x); qb2 = fmaf(v, v, qb2);
                    v = bf_lo(xb[c].y); qb = fmaf(v, v, qb); v = bf_hi(xb[c].y); qb2 = fmaf(v, v, qb2);
                    v = bf_lo(xb[c].z); qb = fmaf(v, v, qb); v = bf_hi(xb[c].z); qb2 = fmaf(v, v, qb2);
                    v = bf_lo(xb[c].w); qb = fmaf(v, v, qb); v = bf_hi(xb[c].w); qb2 = fmaf(v, v, qb2);
                }
            }
            qa += qa2; qb += qb2;
            qa += __shfl_xor_sync(0xffffffffu, qa, 1); qb += __shfl_xor_sync(0xffffffffu, qb, 1);
            qa += __shfl_xor_sync(0xffffffffu, qa, 2); qb += __shfl_xor_sync(0xffffffffu, qb, 2);
            const float ra = rsqrtf(fmaxf(qa * (1.0f / 448.0f) - dma * dma, 0.f) + 1e-5f);
            const float rb = rsqrtf(fmaxf(qb * (1.0f / 448.0f) - dmb * dmb, 0.f) + 1e-5f);
            const int src = ((((g & 3) << 1) | (g >> 2)) << 2);
            rs0 = __shfl_sync(0xffffffffu, ra, src);
            rs1 = __shfl_sync(0xffffffffu, rb, src);
        }
        epoch >>= 7;
        const uint32_t tag = (epoch % 3u) + 1u;
        {
            float s0 = 0.f, q0 = 0.f, s1 = 0.f, q1 = 0.f;
            uint4 p0, p1;
            const uint4* sp = g_stats + ((i * 8 + 2 * t) * 64 + warp * 8 + g);
#pragma unroll
            for (int kb = 0; kb < 7; kb++) {
                mbar_wait(bars + 8 * (B_FULLA + 7 + kb));
                wgmma_fence();
#pragma unroll
                for (int k = 0; k < 4; k++)
                    wgmma_n112<1>(acc_b, dA_xn + ((kb * 16384 + k * 32) >> 4), dB_ra + ((((kb + 8) % 5) * 16384 + k * 2048) >> 4), (kb | k) != 0);
                wgmma_commit();
                wgmma_wait<1>();
                if (sig) mbar_arrive(bars + 8 * (B_DONEA + 6 + kb));
                if (kb == 0) { reg_fence(acc_a); if (threadIdx.x == 0) TS(1); }
                if (kb < 3) {
#pragma unroll
                    for (int b = kb * 5; b < (kb == 2 ? 14 : kb * 5 + 5); b++) {
                        float v0 = gelu_tanh(acc_a[4 * b] * rs0), v1 = gelu_tanh(acc_a[4 * b + 1] * rs0);
                        float v2 = gelu_tanh(acc_a[4 * b + 2] * rs1), v3 = gelu_tanh(acc_a[4 * b + 3] * rs1);
                        s0 += v0 + v1; q0 = fmaf(v0, v0, fmaf(v1, v1, q0));
                        s1 += v2 + v3; q1 = fmaf(v2, v2, fmaf(v3, v3, q1));
                        acc_a[4 * b] = v0; acc_a[4 * b + 1] = v1; acc_a[4 * b + 2] = v2; acc_a[4 * b + 3] = v3;
                    }
                }
                if (kb == 2) {
                    s0 += __shfl_xor_sync(0xffffffffu, s0, 1); q0 += __shfl_xor_sync(0xffffffffu, q0, 1);
                    s1 += __shfl_xor_sync(0xffffffffu, s1, 1); q1 += __shfl_xor_sync(0xffffffffu, q1, 1);
                    s0 += __shfl_xor_sync(0xffffffffu, s0, 2); q0 += __shfl_xor_sync(0xffffffffu, q0, 2);
                    s1 += __shfl_xor_sync(0xffffffffu, s1, 2); q1 += __shfl_xor_sync(0xffffffffu, q1, 2);
                    if (t == 0) {
                        uint4 pk;
                        pk.x = (__float_as_uint(s0) & ~3u) | tag; pk.y = (__float_as_uint(q0) & ~3u) | tag;
                        pk.z = (__float_as_uint(s1) & ~3u) | tag; pk.w = (__float_as_uint(q1) & ~3u) | tag;
                        st_relaxed_v4(g_stats + ((i * 8 + j) * 64 + warp * 8 + g), pk);
                    }
                    if (threadIdx.x == 0) TS(2);
                }
                if (kb == 4) { p0 = ld_relaxed_v4(sp); p1 = ld_relaxed_v4(sp + 64); }
                if (kb == 5) {
                    uint32_t n = 0;
                    while (true) {
                        const uint32_t all = p0.x & p0.y & p0.z & p0.w & p1.x & p1.y & p1.z & p1.w & 3u;
                        const uint32_t any = (p0.x | p0.y | p0.z | p0.w | p1.x | p1.y | p1.z | p1.w) & 3u;
                        if (__all_sync(0xffffffffu, all == tag && any == tag)) break;
                        SPIN_CHECK(n, 1000)
                        p0 = ld_relaxed_v4(sp); p1 = ld_relaxed_v4(sp + 64);
                    }
                    if (threadIdx.x == 0) TS(3);
                    float S0 = __uint_as_float(p0.x) + __uint_as_float(p1.x), Q0 = __uint_as_float(p0.y) + __uint_as_float(p1.y);
                    float S1 = __uint_as_float(p0.z) + __uint_as_float(p1.z), Q1 = __uint_as_float(p0.w) + __uint_as_float(p1.w);
                    S0 += __shfl_xor_sync(0xffffffffu, S0, 1); Q0 += __shfl_xor_sync(0xffffffffu, Q0, 1);
                    S1 += __shfl_xor_sync(0xffffffffu, S1, 1); Q1 += __shfl_xor_sync(0xffffffffu, Q1, 1);
                    S0 += __shfl_xor_sync(0xffffffffu, S0, 2); Q0 += __shfl_xor_sync(0xffffffffu, Q0, 2);
                    S1 += __shfl_xor_sync(0xffffffffu, S1, 2); Q1 += __shfl_xor_sync(0xffffffffu, Q1, 2);
                    const float m0 = S0 * (1.0f / 896.0f), m1 = S1 * (1.0f / 896.0f);
                    const float r0 = rsqrtf(fmaxf(Q0 * (1.0f / 896.0f) - m0 * m0, 0.f) + 1e-5f);
                    const float r1 = rsqrtf(fmaxf(Q1 * (1.0f / 896.0f) - m1 * m1, 0.f) + 1e-5f);
                    const float n0 = -m0 * r0, n1 = -m1 * r1;
                    const int m = lane >> 3;
                    const uint32_t sa = sb + Z2S_OFF + (warp * 2 + (m & 1)) * 1792 + ((m >> 1) * 8 + (lane & 7)) * 16;
#pragma unroll
                    for (int b = 0; b < 14; b += 2) {
                        stmat_x4_t(sa + b * 128,
                                   pack_bf16(fmaf(acc_a[4 * b], r0, n0), fmaf(acc_a[4 * b + 1], r0, n0)),
                                   pack_bf16(fmaf(acc_a[4 * b + 2], r1, n1), fmaf(acc_a[4 * b + 3], r1, n1)),
                                   pack_bf16(fmaf(acc_a[4 * b + 4], r0, n0), fmaf(acc_a[4 * b + 5], r0, n0)),
                                   pack_bf16(fmaf(acc_a[4 * b + 6], r1, n1), fmaf(acc_a[4 * b + 7], r1, n1)));
                    }
                    fence_async_smem();
                    bar_arrive(3 + wg, 160);
                    if (threadIdx.x == 0) TS(4);
                }
            }
        }
        uint32_t z1p[28];
#pragma unroll
        for (int kb = 0; kb < 7; kb++) {
            mbar_wait(bars + 8 * (B_FULLA + 14 + kb));
            wgmma_fence();
#pragma unroll
            for (int k = 0; k < 4; k++)
                wgmma_n168<1>(acc_c, dA_xn + ((kb * 16384 + k * 32) >> 4), dB_ra + (((kb % 3) * 24576 + k * 2048) >> 4), (kb | k) != 0);
            wgmma_commit();
            wgmma_wait<1>();
            if (sig) mbar_arrive(bars + 8 * (B_DONEA + 13 + kb));
            if (kb > 0 && sigr) mbar_arrive_remote(bars + 8 * (B_DONEA + 13 + kb), h ^ 1);
            if (kb == 0) { reg_fence(acc_b); if (threadIdx.x == 0) TS(5); }
#pragma unroll
            for (int b = 2 * kb; b < 2 * kb + 2; b++) {
                z1p[2 * b] = pack_bf16(gelu_tanh(acc_b[4 * b] * rs0), gelu_tanh(acc_b[4 * b + 1] * rs0));
                z1p[2 * b + 1] = pack_bf16(gelu_tanh(acc_b[4 * b + 2] * rs1), gelu_tanh(acc_b[4 * b + 3] * rs1));
            }
        }
        const uint64_t dA_g = mk_desc(sb + wg * 8192, 16, 1024, 1);
        const uint64_t dB_g = mk_desc(sb + 16384, 1792, 128, 0);
        const int row0 = i * 128 + warp * 16 + g;
#pragma unroll
        for (int kb = 0; kb < 3; kb++) {
            mbar_wait(bars + 8 * (B_FULLB + kb));
            if (kb == 0 && threadIdx.x == 0) TS(6);
            wgmma_fence();
#pragma unroll
            for (int k = 0; k < 4; k++)
                wgmma_n112<0>(acc_a, dA_g + ((kb * GSTRIDE + k * 32) >> 4), dB_g + ((kb * GSTRIDE + k * 3584) >> 4), (kb | k) != 0);
            wgmma_commit();
            wgmma_wait<1>();
            const int db = kb == 0 ? B_DONEA + 20 : B_DONEB + kb - 1;
            if (sig) mbar_arrive(bars + 8 * db);
            if (sigr) mbar_arrive_remote(bars + 8 * db, h ^ 1);
            if (kb == 0) { reg_fence(acc_c); if (threadIdx.x == 0) TS(7); }
            uint8_t* qp = g_qkv + ((size_t)((21 * j * 2 + (g & 1)) * 1024 + (row0 >> 1))) * 16 + t * 4;
#pragma unroll
            for (int b = 7 * kb; b < 7 * kb + 7; b++) {
                *reinterpret_cast<uint32_t*>(qp + b * 32768) = pack_bf16(acc_c[4 * b] * rs0, acc_c[4 * b + 1] * rs0);
                *reinterpret_cast<uint32_t*>(qp + b * 32768 + 64) = pack_bf16(acc_c[4 * b + 2] * rs1, acc_c[4 * b + 3] * rs1);
            }
            if (kb == 2) bar_arrive(5 + wg, 160);
        }
        {
            int pos = 3;
#pragma unroll 1
            for (int kb = 3; kb < 32; kb++) {
                const uint32_t ro = greg(pos) >> 4;
                pos = pos == 6 ? 0 : pos + 1;
                mbar_wait(bars + 8 * (B_FULLB + kb));
                wgmma_fence();
#pragma unroll
                for (int k = 0; k < 4; k++) wgmma_n112<0>(acc_a, dA_g + ro + ((k * 32) >> 4), dB_g + ro + ((k * 3584) >> 4), 1);
                wgmma_commit();
                wgmma_wait<1>();
                if (sig) mbar_arrive(bars + 8 * (B_DONEB + kb - 1));
                if (sigr) mbar_arrive_remote(bars + 8 * (B_DONEB + kb - 1), h ^ 1);
            }
        }
        float acc3[28];
        const uint64_t dA_c = mk_desc(sb + wg * GRAN, 1024, 128, 0);
        const uint64_t dB_c = mk_desc(sb, 8192, 1024, 1);
        constexpr uint32_t CA[12] = {3, 4, 1, 5, 0, 5, 2, 0, 5, 3, 2, 4};
        constexpr uint32_t CW[12] = {12, 13, 0, 1, 6, 7, 8, 9, 12, 13, 2, 3};
        const float b0 = __bfloat162float(P.bsp[row0]), b1 = __bfloat162float(P.bsp[row0 + 8]);
        uint32_t xr[14];
        {
            const bf16* xp = P.x + (size_t)row0 * 448 + j * 56 + 2 * t;
#pragma unroll
            for (int b = 0; b < 7; b++) {
                xr[2 * b] = __ldg(reinterpret_cast<const uint32_t*>(xp + 8 * b));
                xr[2 * b + 1] = __ldg(reinterpret_cast<const uint32_t*>(xp + 8 * b + 8 * 448));
            }
        }
#pragma unroll
        for (int n = 0; n < 12; n++) {
            mbar_wait(bars + 8 * (B_FULLCW + n));
            mbar_wait(bars + 8 * (B_FULLCA + 2 * n + wg));
            if (threadIdx.x == 0) TS(16 + n);
            wgmma_fence();
#pragma unroll
            for (int k = 0; k < 7; k++)
                wgmma_n56<1>(acc3, dA_c + ((CA[n] * GSTRIDE + k * 2048) >> 4),
                             dB_c + (((CW[n] >> 1) * GSTRIDE + (CW[n] & 1) * GRAN + k * 2048) >> 4), (n | k) != 0);
            wgmma_commit();
            if (n == 1) {
                mbar_wait(bars + 8 * (B_DONEB + 30));
                const int m = lane >> 3;
                const uint32_t sa = sb + 2 * GSTRIDE + wg * GRAN + (m >> 1) * 1024 + (w * 16 + (m & 1) * 8 + (lane & 7)) * 16;
#pragma unroll
                for (int b = 0; b < 14; b += 2) {
                    stmat_x4(sa + b * 1024,
                             pack_bf16((acc_a[4 * b] + b0) * bf_lo(z1p[2 * b]), (acc_a[4 * b + 1] + b0) * bf_hi(z1p[2 * b])),
                             pack_bf16((acc_a[4 * b + 2] + b1) * bf_lo(z1p[2 * b + 1]), (acc_a[4 * b + 3] + b1) * bf_hi(z1p[2 * b + 1])),
                             pack_bf16((acc_a[4 * b + 4] + b0) * bf_lo(z1p[2 * b + 2]), (acc_a[4 * b + 5] + b0) * bf_hi(z1p[2 * b + 2])),
                             pack_bf16((acc_a[4 * b + 6] + b1) * bf_lo(z1p[2 * b + 3]), (acc_a[4 * b + 7] + b1) * bf_hi(z1p[2 * b + 3])));
                }
                fence_async_smem();
                bar_arrive(7 + wg, 160);
                if (threadIdx.x == 0) TS(9);
            }
            if (n < 4) {
                wgmma_wait<1>();
                const int db = n == 0 ? B_DONEB + 31 : B_DONEC + n - 1;
                if (sig) mbar_arrive(bars + 8 * db);
                if (sigr) mbar_arrive_remote(bars + 8 * db, h ^ 1);
            }
            if (n >= 3 && n < 8) {
                wgmma_wait<0>();
                if (sig) mbar_arrive(bars + 8 * (B_DONEC + n));
                if (sigr) mbar_arrive_remote(bars + 8 * (B_DONEC + n), h ^ 1);
            }
            if (n == 0) { reg_fence(acc_a); if (threadIdx.x == 0) TS(8); }
        }
        wgmma_wait<0>();
        reg_fence(acc3);
        if (threadIdx.x == 0) TS(10);
        {
            bf16* op = P.out + (size_t)row0 * 448 + j * 56 + 2 * t;
#pragma unroll
            for (int b = 0; b < 7; b++) {
                *reinterpret_cast<uint32_t*>(op + 8 * b) = pack_bf16(acc3[4 * b] + bf_lo(xr[2 * b]), acc3[4 * b + 1] + bf_hi(xr[2 * b]));
                *reinterpret_cast<uint32_t*>(op + 8 * b + 8 * 448) = pack_bf16(acc3[4 * b + 2] + bf_lo(xr[2 * b + 1]), acc3[4 * b + 3] + bf_hi(xr[2 * b + 1]));
            }
        }
        if (threadIdx.x == 0) TS(11);
        cluster_arrive();
        cluster_wait();
        if (threadIdx.x == 0) { atomicAdd(&g_done, 1u); TS(12); }
    } else {
        asm volatile("setmaxnreg.dec.sync.aligned.u32 88;");
        {
            const int tid = threadIdx.x - 256;
            for (int b = tid; b < NBARS; b += 128) {
                uint32_t cnt, tx = 0;
                if (b < B_DONEA) { cnt = 1; tx = b < 14 ? 16384 : 24576; }
                else if (b < B_FULLB) cnt = (b - B_DONEA) < 14 ? 2 : 4;
                else if (b < B_DONEB) { cnt = 1; tx = 30720; }
                else if (b < B_FULLCW) cnt = 4;
                else if (b < B_DONEC) { cnt = 1; tx = GRAN; }
                else cnt = 4;
                mbar_init(bars + 8 * b, cnt);
                if (tx) mbar_expect_tx(bars + 8 * b, tx);
            }
            asm volatile("fence.mbarrier_init.release.cluster;" ::: "memory");
            fence_async_smem();
            bar_sync(9, 128);
            cluster_arrive();
        }
        if (warp == 8) {
            if (lane == 0) {
#pragma unroll 1
                for (int n = 0; n < 14; n++) {
                    if (n >= 5) mbar_wait(bars + 8 * (B_DONEA + n - 5));
                    const uint32_t dst = sb + RINGA_OFF + ((n + 1) % 5) * 16384;
                    const int grp = n < 7 ? 8 + j : j, kb = n < 7 ? n : n - 7;
                    tma_3d(dst, &P.tm_win, 0, grp, kb * 64, bars + 8 * (B_FULLA + n));
                    tma_3d(dst + 8192, &P.tm_win, 64, grp, kb * 64, bars + 8 * (B_FULLA + n));
                }
            }
            __syncwarp();
            cluster_wait();
            if (lane == 0) {
                auto ld_qkv = [&](int m, int dep) {
                    mbar_wait(bars + 8 * (B_DONEA + dep));
                    const uint32_t dst = sb + RINGA_OFF + (m % 3) * 24576;
                    tma_3d(dst, &P.tm_wqkv, 0, j, m * 64, bars + 8 * (B_FULLA + 14 + m));
                    tma_3d(dst + 8192, &P.tm_wqkv, 64, j, m * 64, bars + 8 * (B_FULLA + 14 + m));
                    tma_3d(dst + 16384, &P.tm_wqkv, 128, j, m * 64, bars + 8 * (B_FULLA + 14 + m));
                };
                auto ld_sp = [&](int kb, int pos) {
                    tma_2d_mc(sb + greg(pos) + h * 8192, &P.tm_wsp, kb * 64, i * 128 + h * 64, bars + 8 * (B_FULLB + kb));
                };
                ld_qkv(0, 10); ld_qkv(1, 11); ld_qkv(2, 13); ld_qkv(3, 14); ld_qkv(4, 15);
                ld_sp(0, 0);
                ld_qkv(5, 16); ld_qkv(6, 17);
                ld_sp(1, 1);
                mbar_wait(bars + 8 * (B_DONEA + 19));
                ld_sp(2, 2); ld_sp(3, 3);
                mbar_wait(bars + 8 * B_Z2SFREE);
                ld_sp(4, 4);
                mbar_wait(bars + 8 * (B_DONEA + 20));
                ld_sp(5, 5); ld_sp(6, 6);
                int pos = 0;
#pragma unroll 1
                for (int kb = 7; kb < 32; kb++) {
                    mbar_wait(bars + 8 * (B_DONEB + kb - 7));
                    ld_sp(kb, pos);
                    pos = pos == 6 ? 0 : pos + 1;
                }
                auto ld_w = [&](int n, uint32_t slot) {
                    const uint32_t dst = sb + (slot >> 1) * GSTRIDE + (slot & 1) * GRAN;
                    if (n < 4) tma_3d(dst, &P.tm_wo, 0, j, n * 112, bars + 8 * (B_FULLCW + n));
                    else tma_3d(dst, &P.tm_wout, 0, j, ((2 * jj + n - 4) & 7) * 112, bars + 8 * (B_FULLCW + n));
                };
                mbar_wait(bars + 8 * (B_DONEB + 25));
                ld_w(0, 12); ld_w(1, 13);
                mbar_wait(bars + 8 * (B_DONEB + 28));
                ld_w(2, 0); ld_w(3, 1);
                mbar_wait(bars + 8 * (B_DONEC + 0));
                ld_w(4, 6); ld_w(5, 7);
                mbar_wait(bars + 8 * (B_DONEC + 1));
                ld_w(6, 8); ld_w(7, 9); ld_w(8, 12); ld_w(9, 13);
                mbar_wait(bars + 8 * (B_DONEC + 2));
                ld_w(10, 2); ld_w(11, 3);
            }
        } else if (warp == 9) {
            cluster_wait();
            const unsigned tgt = (epoch >> 7) + 1u;
            {
                unsigned ready = 0;
                int pos = 0;
#pragma unroll 1
                for (int kb = 0; kb < 32; kb++) {
                    uint32_t n = 0;
                    while (!((ready >> kb) & 1u)) {
                        ready = __ballot_sync(0xffffffffu, ld_acquire(g_z2flag + j * 32 + lane) == tgt);
                        SPIN_CHECK(n, 1100 + kb)
                        if ((ready >> kb) & 1u) fence_async_global();
                    }
                    if (lane == 0) {
                        if (kb == 0) TS(32);
                        if (kb >= 7) mbar_wait(bars + 8 * (B_DONEB + kb - 7));
                        else {
                            mbar_wait(bars + 8 * (B_DONEA + (kb == 0 ? 15 : kb == 1 ? 17 : kb < 5 ? 19 : 20)));
                            if (kb == 4) mbar_wait(bars + 8 * B_Z2SFREE);
                        }
                        bulk_load(sb + greg(pos) + 16384, g_z2t + (size_t)((kb >> 1) * 8 + j) * 28672 + (kb & 1) * GRAN, GRAN, bars + 8 * (B_FULLB + kb));
                    }
                    pos = pos == 6 ? 0 : pos + 1;
                    __syncwarp();
                }
            }
            {
                constexpr uint64_t CA_P = 0x423502505143ull;
                unsigned ready = 0;
                const uint8_t* src = g_ou + (size_t)(i * 2 + h) * 168 * 1024;
#pragma unroll 1
                for (int n = 0; n < 12; n++) {
                    const int jt = (2 * jj + n - 4) & 7;
                    const unsigned need = n < 4 ? (3u << (8 + 2 * n)) : (1u << jt);
                    uint32_t cnt = 0;
                    while ((ready & need) != need) {
                        ready = __ballot_sync(0xffffffffu, ld_acquire(g_ouflag + (i * 2 + h) * 16 + (lane & 15)) == tgt);
                        SPIN_CHECK(cnt, 1200 + n)
                        if ((ready & need) == need) fence_async_global();
                    }
                    if (lane == 0) {
                        TS(33 + n);
                        int dep;
                        switch (n) {
                            case 0: dep = B_DONEB + 26; break;
                            case 1: dep = B_DONEB + 27; break;
                            case 2: dep = B_DONEB + 29; break;
                            case 3: dep = B_DONEB + 31; break;
                            case 4: case 5: dep = B_DONEC + 3; break;
                            case 6: dep = B_USTFREE; break;
                            case 7: dep = B_DONEC + 4; break;
                            case 8: case 9: dep = B_DONEC + 5; break;
                            case 10: dep = B_DONEC + 6; break;
                            default: dep = B_DONEC + 7; break;
                        }
                        mbar_wait(bars + 8 * dep);
                        const uint32_t reg = (uint32_t)(CA_P >> (4 * n)) & 7u;
                        bulk_load_mc(sb + reg * GSTRIDE + h * GRAN, src + (size_t)(n < 4 ? n : 4 + jt) * GRAN, GRAN, bars + 8 * (B_FULLCA + 2 * n + h));
                    }
                    __syncwarp();
                }
            }
        } else {
            const int a = warp - 10;
            const int hb = i * 2 + a;
            if (a == 0) {
                if (lane == 0) l2_prefetch(reinterpret_cast<const uint8_t*>(P.win) + (size_t)blockIdx.x * 12544, 12544);
                if (lane == 1) l2_prefetch(reinterpret_cast<const uint8_t*>(P.wqkv) + (size_t)blockIdx.x * 9408, 9408);
            }
            cluster_wait();
            __nanosleep(1000);
            l2_prefetch(reinterpret_cast<const uint8_t*>(P.wsp) + (size_t)blockIdx.x * 65536 + (a * 32 + lane) * 1024, 1024);
            if (a == 1) {
                if (lane == 0) l2_prefetch(reinterpret_cast<const uint8_t*>(P.wo) + (size_t)blockIdx.x * 3136, 3136);
                if (lane == 1) l2_prefetch(reinterpret_cast<const uint8_t*>(P.wout) + (size_t)blockIdx.x * 6272, 6272);
            }
            const unsigned tgt = (epoch >> 7) + 1u;
            bar_sync(3 + a, 160);
            if (lane == 0) {
                bulk_store(g_z2t + (size_t)(i * 8 + j) * 28672 + a * GRAN, sb + Z2S_OFF + a * GRAN, GRAN);
                asm volatile("cp.async.bulk.wait_group.read 0;" ::: "memory");
                mbar_arrive(bars + 8 * B_Z2SFREE);
                mbar_arrive_remote(bars + 8 * B_Z2SFREE, h ^ 1);
                asm volatile("cp.async.bulk.wait_group 0;" ::: "memory");
                fence_async_global();
                st_release(g_z2flag + j * 32 + hb, tgt);
                if (a == 0) TS(48);
            }
            __syncwarp();
            bar_sync(5 + a, 160);
            if (lane == 0) { st_release(g_qflag + hb * 8 + j, tgt); if (a == 0) TS(49); }
            __syncwarp();
            {
                const int fi = (hb > 0 ? hb - 1 : 0) * 8 + (lane & 15) - (hb > 0 ? 0 : ((lane & 8) ? 8 : 0));
                uint32_t n = 0;
                while (!__all_sync(0xffffffffu, ld_acquire(g_qflag + fi) == tgt)) { SPIN_CHECK(n, 1300) }
            }
            if (lane == 0 && a == 0) TS(50);
#pragma unroll 1
            for (int task = 0; task < 8; task++) {
                const int e = task & 1, p = (task >> 1) & 1, blk = task >> 2;
                const int P0 = hb * 32 + blk * 16;
                const int c = 7 * j + 3 * e + t;
                const uint8_t* base = g_qkv + (size_t)((c * 2 + p) * 1024) * 16;
                uint4 qa = ld_v4(base + (P0 + g) * 16), qb = ld_v4(base + (P0 + g + 8) * 16);
                uint4 kk[3], vv[3];
#pragma unroll
                for (int n = 0; n < 3; n++) {
                    const int pi = max(P0 - 8 + 8 * n + g, 0);
                    kk[n] = ld_v4(base + (size_t)56 * 32768 + pi * 16);
                    vv[n] = ld_v4(base + (size_t)112 * 32768 + pi * 16);
                }
                if (e == 0 && t == 3) { qa.z = qa.w = qb.z = qb.w = 0u; }
                if (e == 1 && t == 0) { qa.x = qa.y = qb.x = qb.y = 0u; }
                float s[3][4];
#pragma unroll
                for (int n = 0; n < 3; n++) {
                    s[n][0] = s[n][1] = s[n][2] = s[n][3] = 0.f;
                    mma16816(s[n], qa.x, qb.x, qa.y, qb.y, kk[n].x, kk[n].y);
                    mma16816(s[n], qa.z, qb.z, qa.w, qb.w, kk[n].z, kk[n].w);
                }
                const float NEG = -3.0e38f;
                const bool first = (P0 == 0);
                float l0[4], l1[4];
                l0[0] = (2 * t >= g + 1 && !first) ? s[0][0] : NEG;
                l0[1] = (2 * t + 1 >= g + 1 && !first) ? s[0][1] : NEG;
                l0[2] = (2 * t <= g) ? s[1][0] : NEG;
                l0[3] = (2 * t + 1 <= g) ? s[1][1] : NEG;
                l1[0] = (2 * t >= g + 1) ? s[1][2] : NEG;
                l1[1] = (2 * t + 1 >= g + 1) ? s[1][3] : NEG;
                l1[2] = (2 * t <= g) ? s[2][2] : NEG;
                l1[3] = (2 * t + 1 <= g) ? s[2][3] : NEG;
                float m0 = fmaxf(fmaxf(l0[0], l0[1]), fmaxf(l0[2], l0[3]));
                float m1 = fmaxf(fmaxf(l1[0], l1[1]), fmaxf(l1[2], l1[3]));
                m0 = fmaxf(m0, __shfl_xor_sync(0xffffffffu, m0, 1)); m1 = fmaxf(m1, __shfl_xor_sync(0xffffffffu, m1, 1));
                m0 = fmaxf(m0, __shfl_xor_sync(0xffffffffu, m0, 2)); m1 = fmaxf(m1, __shfl_xor_sync(0xffffffffu, m1, 2));
                const float sc = 0.18898223650461362f * 1.4426950408889634f;
                float d0 = 0.f, d1 = 0.f;
#pragma unroll
                for (int k = 0; k < 4; k++) {
                    l0[k] = l0[k] == NEG ? 0.f : ex2((l0[k] - m0) * sc); d0 += l0[k];
                    l1[k] = l1[k] == NEG ? 0.f : ex2((l1[k] - m1) * sc); d1 += l1[k];
                }
                d0 += __shfl_xor_sync(0xffffffffu, d0, 1); d1 += __shfl_xor_sync(0xffffffffu, d1, 1);
                d0 += __shfl_xor_sync(0xffffffffu, d0, 2); d1 += __shfl_xor_sync(0xffffffffu, d1, 2);
                d0 = 1.0f / d0; d1 = 1.0f / d1;
                const uint32_t pa0 = pack_bf16(l0[0] * d0, l0[1] * d0), pa2 = pack_bf16(l0[2] * d0, l0[3] * d0);
                const uint32_t pa3 = pack_bf16(l1[0] * d1, l1[1] * d1), pb1 = pack_bf16(l1[2] * d1, l1[3] * d1);
                float o[4][4];
#pragma unroll
                for (int k = 0; k < 4; k++) o[k][0] = o[k][1] = o[k][2] = o[k][3] = 0.f;
                mma16816(o[0], pa0, 0u, pa2, pa3, movmat(vv[0].x), movmat(vv[1].x)); mma1688(o[0], 0u, pb1, movmat(vv[2].x));
                mma16816(o[1], pa0, 0u, pa2, pa3, movmat(vv[0].y), movmat(vv[1].y)); mma1688(o[1], 0u, pb1, movmat(vv[2].y));
                mma16816(o[2], pa0, 0u, pa2, pa3, movmat(vv[0].z), movmat(vv[1].z)); mma1688(o[2], 0u, pb1, movmat(vv[2].z));
                mma16816(o[3], pa0, 0u, pa2, pa3, movmat(vv[0].w), movmat(vv[1].w)); mma1688(o[3], 0u, pb1, movmat(vv[2].w));
                uint8_t* op = g_ou + ((size_t)(hb * 168 + c) * 64 + 2 * (16 * blk + g) + p) * 16;
                const uint2 lo0 = make_uint2(pack_bf16(o[0][0], o[0][1]), pack_bf16(o[1][0], o[1][1]));
                const uint2 hi0 = make_uint2(pack_bf16(o[2][0], o[2][1]), pack_bf16(o[3][0], o[3][1]));
                const uint2 lo1 = make_uint2(pack_bf16(o[0][2], o[0][3]), pack_bf16(o[1][2], o[1][3]));
                const uint2 hi1 = make_uint2(pack_bf16(o[2][2], o[2][3]), pack_bf16(o[3][2], o[3][3]));
                if (!(e == 1 && t == 0)) { *reinterpret_cast<uint2*>(op) = lo0; *reinterpret_cast<uint2*>(op + 256) = lo1; }
                if (!(e == 0 && t == 3)) { *reinterpret_cast<uint2*>(op + 8) = hi0; *reinterpret_cast<uint2*>(op + 264) = hi1; }
            }
            fence_async_global();
            __syncwarp();
            if (lane == 0) { st_release(g_ouflag + hb * 16 + 8 + j, tgt); if (a == 0) TS(51); }
            bar_sync(7 + a, 160);
            if (lane == 0) {
                bulk_store(g_ou + ((size_t)hb * 168 + 56 + 14 * j) * 1024, sb + 2 * GSTRIDE + a * GRAN, GRAN);
                asm volatile("cp.async.bulk.wait_group.read 0;" ::: "memory");
                mbar_arrive(bars + 8 * B_USTFREE);
                mbar_arrive_remote(bars + 8 * B_USTFREE, h ^ 1);
                asm volatile("cp.async.bulk.wait_group 0;" ::: "memory");
                fence_async_global();
                st_release(g_ouflag + hb * 16 + j, tgt);
                if (a == 0) TS(52);
            }
        }
        __syncwarp();
        cluster_arrive();
        cluster_wait();
    }
}

typedef CUresult (*PFN_encodeTiled)(CUtensorMap*, CUtensorMapDataType, cuuint32_t, void*, const cuuint64_t*, const cuuint64_t*,
                                    const cuuint32_t*, const cuuint32_t*, CUtensorMapInterleave, CUtensorMapSwizzle,
                                    CUtensorMapL2promotion, CUtensorMapFloatOOBfill);

void make_map(PFN_encodeTiled enc, CUtensorMap* tm, const void* ptr, int rank, const cuuint64_t* dims, const cuuint64_t* strides,
              const cuuint32_t* box) {
    cuuint32_t es[3] = {1, 1, 1};
    enc(tm, CU_TENSOR_MAP_DATA_TYPE_BFLOAT16, rank, const_cast<void*>(ptr), dims, strides, box, es, CU_TENSOR_MAP_INTERLEAVE_NONE,
        CU_TENSOR_MAP_SWIZZLE_128B, CU_TENSOR_MAP_L2_PROMOTION_L2_128B, CU_TENSOR_MAP_FLOAT_OOB_FILL_NONE);
}

}

extern "C" void kernel_launch(void* const* d_in, const int* in_sizes, int n_in, void* d_out, int out_size) {
    (void)in_sizes; (void)n_in; (void)out_size;
    PFN_encodeTiled enc = nullptr;
    cudaDriverEntryPointQueryResult st;
    cudaGetDriverEntryPoint("cuTensorMapEncodeTiled", (void**)&enc, cudaEnableDefault, &st);
    Params P;
    P.x = (const bf16*)d_in[0];
    P.wqkv = (const bf16*)d_in[1];
    P.wo = (const bf16*)d_in[2];
    P.win = (const bf16*)d_in[4];
    P.wsp = (const bf16*)d_in[5];
    P.bsp = (const bf16*)d_in[6];
    P.wout = (const bf16*)d_in[7];
    P.out = (bf16*)d_out;
    {
        cuuint64_t d[3] = {112, 16, 448}, s[2] = {224, 3584}; cuuint32_t b[3] = {64, 1, 64};
        make_map(enc, &P.tm_win, P.win, 3, d, s, b);
    }
    {
        cuuint64_t d[3] = {168, 8, 448}, s[2] = {336, 2688}; cuuint32_t b[3] = {64, 1, 64};
        make_map(enc, &P.tm_wqkv, P.wqkv, 3, d, s, b);
    }
    {
        cuuint64_t d[2] = {2048, 2048}, s[1] = {4096}; cuuint32_t b[2] = {64, 64};
        make_map(enc, &P.tm_wsp, P.wsp, 2, d, s, b);
    }
    {
        cuuint64_t d[3] = {56, 8, 448}, s[2] = {112, 896}; cuuint32_t b[3] = {64, 1, 112};
        make_map(enc, &P.tm_wo, P.wo, 3, d, s, b);
    }
    {
        cuuint64_t d[3] = {56, 8, 896}, s[2] = {112, 896}; cuuint32_t b[3] = {64, 1, 112};
        make_map(enc, &P.tm_wout, P.wout, 3, d, s, b);
    }
    cudaFuncSetAttribute(fused_kernel, cudaFuncAttributeMaxDynamicSharedMemorySize, SMEM_BYTES);
    fused_kernel<<<128, 384, SMEM_BYTES>>>(P);
}
```

```cpp
#include <cuda_runtime.h>
#include <cuda_bf16.h>
#include <cuda.h>
#include <stdint.h>

namespace {

typedef __nv_bfloat16 bf16;

__device__ __align__(1024) uint8_t g_z2t[16 * 8 * 28672];
__device__ __align__(1024) uint8_t g_ou[16 * 2 * 168 * 1024];
__device__ __align__(1024) uint8_t g_qkv[168 * 2 * 1024 * 16];
__device__ __align__(128) uint4 g_stats[16 * 8 * 64];
__device__ __align__(128) unsigned g_z2flag[8 * 32];
__device__ __align__(128) unsigned g_qflag[32 * 8];
__device__ __align__(128) unsigned g_ouflag[32 * 16];
__device__ unsigned g_done;
#define TS(k) do {} while (0)
#define SPIN_CHECK(n, code) if (++n > (1u << 20)) __trap();

constexpr uint32_t XN_OFF = 0;
constexpr uint32_t RINGA_OFF = 114688;
constexpr uint32_t Z2S_OFF = 196608;
constexpr uint32_t GSTRIDE = 30720;
constexpr uint32_t GRAN = 14336;
constexpr uint32_t BAR_OFF = 225280;
constexpr int B_FULLA = 0, B_DONEA = 21, B_FULLB = 42, B_DONEB = 74, B_FULLCW = 106, B_FULLCA = 118,
              B_DONEC = 142, B_Z2SFREE = 154, B_USTFREE = 155, B_FULLX = 156, NBARS = 163;
constexpr uint32_t SMEM_BYTES = BAR_OFF + NBARS * 8 + 1024;
constexpr uint32_t GORDER = 0x4365210u;

__device__ __forceinline__ uint32_t smem_u32(const void* p) { return (uint32_t)__cvta_generic_to_shared(p); }
__device__ __forceinline__ void mbar_init(uint32_t bar, uint32_t count) {
    asm volatile("mbarrier.init.shared::cta.b64 [%0], %1;" ::"r"(bar), "r"(count) : "memory");
}
__device__ __forceinline__ void mbar_expect_tx(uint32_t bar, uint32_t bytes) {
    asm volatile("mbarrier.arrive.expect_tx.shared::cta.b64 _, [%0], %1;" ::"r"(bar), "r"(bytes) : "memory");
}
__device__ __forceinline__ void mbar_arrive(uint32_t bar) {
    asm volatile("mbarrier.arrive.shared::cta.b64 _, [%0];" ::"r"(bar) : "memory");
}
__device__ __forceinline__ void mbar_arrive_remote(uint32_t bar, uint32_t cta) {
    asm volatile("{\n.reg .b32 ra;\nmapa.shared::cluster.u32 ra, %0, %1;\nmbarrier.arrive.shared::cluster.b64 _, [ra];\n}\n" ::"r"(bar), "r"(cta) : "memory");
}
__device__ __forceinline__ void mbar_wait(uint32_t bar) {
    asm volatile("{\n.reg .pred p;\n.reg .u32 n;\nmov.u32 n, 0;\n"
                 "W_LOOP:\nmbarrier.try_wait.parity.shared::cta.b64 p, [%0], 0;\n@p bra W_DONE;\n"
                 "add.u32 n, n, 1;\nsetp.lt.u32 p, n, 0x100000;\n@p bra W_LOOP;\ntrap;\nW_DONE:\n}\n" ::"r"(bar) : "memory");
}
__device__ __forceinline__ void tma_3d(uint32_t dst, const CUtensorMap* tm, int c0, int c1, int c2, uint32_t bar) {
    asm volatile("cp.async.bulk.tensor.3d.shared::cluster.global.mbarrier::complete_tx::bytes [%0], [%1, {%3, %4, %5}], [%2];"
                 ::"r"(dst), "l"(tm), "r"(bar), "r"(c0), "r"(c1), "r"(c2) : "memory");
}
__device__ __forceinline__ void tma_2d(uint32_t dst, const CUtensorMap* tm, int c0, int c1, uint32_t bar) {
    asm volatile("cp.async.bulk.tensor.2d.shared::cluster.global.mbarrier::complete_tx::bytes [%0], [%1, {%3, %4}], [%2];"
                 ::"r"(dst), "l"(tm), "r"(bar), "r"(c0), "r"(c1) : "memory");
}
__device__ __forceinline__ void tma_2d_mc(uint32_t dst, const CUtensorMap* tm, int c0, int c1, uint32_t bar) {
    asm volatile("cp.async.bulk.tensor.2d.shared::cluster.global.mbarrier::complete_tx::bytes.multicast::cluster [%0], [%1, {%3, %4}], [%2], %5;"
                 ::"r"(dst), "l"(tm), "r"(bar), "r"(c0), "r"(c1), "h"((uint16_t)3) : "memory");
}
__device__ __forceinline__ void bulk_load(uint32_t dst, const void* src, uint32_t bytes, uint32_t bar) {
    asm volatile("cp.async.bulk.shared::cluster.global.mbarrier::complete_tx::bytes [%0], [%1], %2, [%3];"
                 ::"r"(dst), "l"(src), "r"(bytes), "r"(bar) : "memory");
}
__device__ __forceinline__ void bulk_load_mc(uint32_t dst, const void* src, uint32_t bytes, uint32_t bar) {
    asm volatile("cp.async.bulk.shared::cluster.global.mbarrier::complete_tx::bytes.multicast::cluster [%0], [%1], %2, [%3], %4;"
                 ::"r"(dst), "l"(src), "r"(bytes), "r"(bar), "h"((uint16_t)3) : "memory");
}
__device__ __forceinline__ void bulk_store(void* dst, uint32_t src, uint32_t bytes) {
    asm volatile("cp.async.bulk.global.shared::cta.bulk_group [%0], [%1], %2;" ::"l"(dst), "r"(src), "r"(bytes) : "memory");
    asm volatile("cp.async.bulk.commit_group;" ::: "memory");
}
__device__ __forceinline__ void l2_prefetch(const void* p, uint32_t bytes) {
    asm volatile("cp.async.bulk.prefetch.L2.global [%0], %1;" ::"l"(p), "r"(bytes) : "memory");
}
__device__ __forceinline__ void wgmma_fence() { asm volatile("wgmma.fence.sync.aligned;" ::: "memory"); }
__device__ __forceinline__ void wgmma_commit() { asm volatile("wgmma.commit_group.sync.aligned;" ::: "memory"); }
template <int N> __device__ __forceinline__ void wgmma_wait() { asm volatile("wgmma.wait_group.sync.aligned %0;" ::"n"(N) : "memory"); }
template <int N> __device__ __forceinline__ void reg_fence(float (&d)[N]) {
#pragma unroll
    for (int k = 0; k < N; k++) asm volatile("" : "+f"(d[k])::"memory");
}
__device__ __forceinline__ uint32_t dlo(uint32_t addr, uint32_t lbo) { return ((addr & 0x3FFFF) >> 4) | ((lbo >> 4) << 16); }
constexpr uint32_t HI_SW128 = (1024 >> 4) | (1u << 30);
constexpr uint32_t HI_NOSW = (128 >> 4);
__device__ __forceinline__ void bar_sync(int id, int n) { asm volatile("bar.sync %0, %1;" ::"r"(id), "r"(n) : "memory"); }
__device__ __forceinline__ void bar_arrive(int id, int n) { asm volatile("bar.arrive %0, %1;" ::"r"(id), "r"(n) : "memory"); }
__device__ __forceinline__ void fence_async_smem() { asm volatile("fence.proxy.async.shared::cta;" ::: "memory"); }
__device__ __forceinline__ void fence_async_global() { asm volatile("fence.proxy.async.global;" ::: "memory"); }
__device__ __forceinline__ void cluster_arrive() { asm volatile("barrier.cluster.arrive.release.aligned;" ::: "memory"); }
__device__ __forceinline__ void cluster_arrive_relaxed() { asm volatile("barrier.cluster.arrive.relaxed.aligned;" ::: "memory"); }
__device__ __forceinline__ void mbar_arrive_cl(uint32_t cluster_addr) {
    asm volatile("mbarrier.arrive.shared::cluster.b64 _, [%0];" ::"r"(cluster_addr) : "memory");
}
__device__ __forceinline__ void cluster_wait() { asm volatile("barrier.cluster.wait.acquire.aligned;" ::: "memory"); }
__device__ __forceinline__ unsigned ld_acquire(const unsigned* p) {
    unsigned v; asm volatile("ld.acquire.gpu.global.u32 %0, [%1];" : "=r"(v) : "l"(p) : "memory"); return v;
}
__device__ __forceinline__ void st_release(unsigned* p, unsigned v) {
    asm volatile("st.release.gpu.global.u32 [%0], %1;" ::"l"(p), "r"(v) : "memory");
}
__device__ __forceinline__ uint4 ld_relaxed_v4(const uint4* p) {
    uint4 v; asm volatile("ld.relaxed.gpu.global.v4.u32 {%0,%1,%2,%3}, [%4];" : "=r"(v.x), "=r"(v.y), "=r"(v.z), "=r"(v.w) : "l"(p) : "memory"); return v;
}
__device__ __forceinline__ void st_relaxed_v4(uint4* p, uint4 v) {
    asm volatile("st.relaxed.gpu.global.v4.u32 [%0], {%1,%2,%3,%4};" ::"l"(p), "r"(v.x), "r"(v.y), "r"(v.z), "r"(v.w) : "memory");
}
__device__ __forceinline__ uint4 ld_nc_v4(const void* p) {
    uint4 v; asm volatile("ld.global.nc.L1::no_allocate.v4.u32 {%0,%1,%2,%3}, [%4];" : "=r"(v.x), "=r"(v.y), "=r"(v.z), "=r"(v.w) : "l"(p)); return v;
}
__device__ __forceinline__ uint4 ld_v4(const void* p) {
    uint4 v; asm volatile("ld.global.v4.u32 {%0,%1,%2,%3}, [%4];" : "=r"(v.x), "=r"(v.y), "=r"(v.z), "=r"(v.w) : "l"(p) : "memory"); return v;
}
__device__ __forceinline__ uint4 lds_v4(uint32_t a) {
    uint4 v; asm volatile("ld.shared.v4.u32 {%0,%1,%2,%3}, [%4];" : "=r"(v.x), "=r"(v.y), "=r"(v.z), "=r"(v.w) : "r"(a) : "memory"); return v;
}
__device__ __forceinline__ unsigned ld_relaxed(const unsigned* p) {
    unsigned v; asm volatile("ld.relaxed.gpu.global.u32 %0, [%1];" : "=r"(v) : "l"(p) : "memory"); return v;
}
__device__ __forceinline__ void sts_v4(uint32_t a, uint4 v) {
    asm volatile("st.shared.v4.u32 [%0], {%1,%2,%3,%4};" ::"r"(a), "r"(v.x), "r"(v.y), "r"(v.z), "r"(v.w) : "memory");
}
__device__ __forceinline__ uint32_t pack_bf16(float lo, float hi) {
    uint32_t r; asm("cvt.rn.bf16x2.f32 %0, %1, %2;" : "=r"(r) : "f"(hi), "f"(lo)); return r;
}
__device__ __forceinline__ float bf_lo(uint32_t r) { return __uint_as_float(r << 16); }
__device__ __forceinline__ float bf_hi(uint32_t r) { return __uint_as_float(r & 0xffff0000u); }
__device__ __forceinline__ uint32_t sub_bf16x2(uint32_t a, uint32_t b) {
    uint32_t r; asm("sub.rn.bf16x2 %0, %1, %2;" : "=r"(r) : "r"(a), "r"(b)); return r;
}
__device__ __forceinline__ void mma16816(float (&c)[4], uint32_t a0, uint32_t a1, uint32_t a2, uint32_t a3, uint32_t b0, uint32_t b1) {
    asm("mma.sync.aligned.m16n8k16.row.col.f32.bf16.bf16.f32 {%0,%1,%2,%3}, {%4,%5,%6,%7}, {%8,%9}, {%0,%1,%2,%3};"
        : "+f"(c[0]), "+f"(c[1]), "+f"(c[2]), "+f"(c[3]) : "r"(a0), "r"(a1), "r"(a2), "r"(a3), "r"(b0), "r"(b1));
}
__device__ __forceinline__ void mma1688(float (&c)[4], uint32_t a0, uint32_t a1, uint32_t b0) {
    asm("mma.sync.aligned.m16n8k8.row.col.f32.bf16.bf16.f32 {%0,%1,%2,%3}, {%4,%5}, {%6}, {%0,%1,%2,%3};"
        : "+f"(c[0]), "+f"(c[1]), "+f"(c[2]), "+f"(c[3]) : "r"(a0), "r"(a1), "r"(b0));
}
__device__ __forceinline__ uint32_t movmat(uint32_t a) {
    uint32_t d; asm("movmatrix.sync.aligned.m8n8.trans.b16 %0, %1;" : "=r"(d) : "r"(a)); return d;
}
__device__ __forceinline__ void stmat_x4(uint32_t a, uint32_t r0, uint32_t r1, uint32_t r2, uint32_t r3) {
    asm volatile("stmatrix.sync.aligned.m8n8.x4.shared.b16 [%0], {%1,%2,%3,%4};" ::"r"(a), "r"(r0), "r"(r1), "r"(r2), "r"(r3) : "memory");
}
__device__ __forceinline__ void stmat_x4_t(uint32_t a, uint32_t r0, uint32_t r1, uint32_t r2, uint32_t r3) {
    asm volatile("stmatrix.sync.aligned.m8n8.x4.trans.shared.b16 [%0], {%1,%2,%3,%4};" ::"r"(a), "r"(r0), "r"(r1), "r"(r2), "r"(r3) : "memory");
}
struct GeluC { float c0, c1, hr; };
__device__ __forceinline__ GeluC gelu_consts(float r) {
    GeluC c; c.c0 = 0.797884560803f * r; c.c1 = 0.035677408136f * r * r * r; c.hr = 0.5f * r; return c;
}
__device__ __forceinline__ float gelu_s(float a, const GeluC& c) {
    const float p = fmaf(a * a, c.c1, c.c0);
    float th; asm("tanh.approx.f32 %0, %1;" : "=f"(th) : "f"(a * p));
    const float h = a * c.hr;
    return fmaf(h, th, h);
}
__device__ __forceinline__ float ex2(float x) { float r; asm("ex2.approx.ftz.f32 %0, %1;" : "=f"(r) : "f"(x)); return r; }

template <int TB, uint32_t AHI, uint32_t BHI>
__device__ __forceinline__ void wgmma_n56(float (&d)[28], uint32_t alo, uint32_t blo, bool acc) {
    if (acc) {
        asm volatile("{\n.reg .b64 da, db;\nmov.b64 da, {%28, %31};\nmov.b64 db, {%29, %32};\n"
            "wgmma.mma_async.sync.aligned.m64n56k16.f32.bf16.bf16 {%0, %1, %2, %3, %4, %5, %6, %7, %8, %9, %10, %11, %12, %13, %14, %15, %16, %17, %18, %19, %20, %21, %22, %23, %24, %25, %26, %27}, da, db, 1, 1, 1, 0, %30;\n}\n"
            : "+f"(d[0]), "+f"(d[1]), "+f"(d[2]), "+f"(d[3]), "+f"(d[4]), "+f"(d[5]), "+f"(d[6]), "+f"(d[7]), "+f"(d[8]), "+f"(d[9]), "+f"(d[10]), "+f"(d[11]), "+f"(d[12]), "+f"(d[13]), "+f"(d[14]), "+f"(d[15]), "+f"(d[16]), "+f"(d[17]), "+f"(d[18]), "+f"(d[19]), "+f"(d[20]), "+f"(d[21]), "+f"(d[22]), "+f"(d[23]), "+f"(d[24]), "+f"(d[25]), "+f"(d[26]), "+f"(d[27])
            : "r"(alo), "r"(blo), "n"(TB), "n"(AHI), "n"(BHI));
    } else {
        asm volatile("{\n.reg .b64 da, db;\nmov.b64 da, {%28, %31};\nmov.b64 db, {%29, %32};\n"
            "wgmma.mma_async.sync.aligned.m64n56k16.f32.bf16.bf16 {%0, %1, %2, %3, %4, %5, %6, %7, %8, %9, %10, %11, %12, %13, %14, %15, %16, %17, %18, %19, %20, %21, %22, %23, %24, %25, %26, %27}, da, db, 0, 1, 1, 0, %30;\n}\n"
            : "=f"(d[0]), "=f"(d[1]), "=f"(d[2]), "=f"(d[3]), "=f"(d[4]), "=f"(d[5]), "=f"(d[6]), "=f"(d[7]), "=f"(d[8]), "=f"(d[9]), "=f"(d[10]), "=f"(d[11]), "=f"(d[12]), "=f"(d[13]), "=f"(d[14]), "=f"(d[15]), "=f"(d[16]), "=f"(d[17]), "=f"(d[18]), "=f"(d[19]), "=f"(d[20]), "=f"(d[21]), "=f"(d[22]), "=f"(d[23]), "=f"(d[24]), "=f"(d[25]), "=f"(d[26]), "=f"(d[27])
            : "r"(alo), "r"(blo), "n"(TB), "n"(AHI), "n"(BHI));
    }
}
template <int TB, uint32_t AHI, uint32_t BHI>
__device__ __forceinline__ void wgmma_n56_p(float (&d)[28], uint32_t alo, uint32_t blo, int acc) {
    asm volatile("{\n.reg .b64 da, db;\n.reg .pred p;\nsetp.ne.b32 p, %33, 0;\nmov.b64 da, {%28, %31};\nmov.b64 db, {%29, %32};\n"
        "wgmma.mma_async.sync.aligned.m64n56k16.f32.bf16.bf16 {%0, %1, %2, %3, %4, %5, %6, %7, %8, %9, %10, %11, %12, %13, %14, %15, %16, %17, %18, %19, %20, %21, %22, %23, %24, %25, %26, %27}, da, db, p, 1, 1, 0, %30;\n}\n"
        : "+f"(d[0]), "+f"(d[1]), "+f"(d[2]), "+f"(d[3]), "+f"(d[4]), "+f"(d[5]), "+f"(d[6]), "+f"(d[7]), "+f"(d[8]), "+f"(d[9]), "+f"(d[10]), "+f"(d[11]), "+f"(d[12]), "+f"(d[13]), "+f"(d[14]), "+f"(d[15]), "+f"(d[16]), "+f"(d[17]), "+f"(d[18]), "+f"(d[19]), "+f"(d[20]), "+f"(d[21]), "+f"(d[22]), "+f"(d[23]), "+f"(d[24]), "+f"(d[25]), "+f"(d[26]), "+f"(d[27])
        : "r"(alo), "r"(blo), "n"(TB), "n"(AHI), "n"(BHI), "r"(acc));
}
template <int TB, uint32_t AHI, uint32_t BHI>
__device__ __forceinline__ void wgmma_n112(float (&d)[56], uint32_t alo, uint32_t blo, bool acc) {
    if (acc) {
        asm volatile("{\n.reg .b64 da, db;\nmov.b64 da, {%56, %59};\nmov.b64 db, {%57, %60};\n"
            "wgmma.mma_async.sync.aligned.m64n112k16.f32.bf16.bf16 {%0, %1, %2, %3, %4, %5, %6, %7, %8, %9, %10, %11, %12, %13, %14, %15, %16, %17, %18, %19, %20, %21, %22, %23, %24, %25, %26, %27, %28, %29, %30, %31, %32, %33, %34, %35, %36, %37, %38, %39, %40, %41, %42, %43, %44, %45, %46, %47, %48, %49, %50, %51, %52, %53, %54, %55}, da, db, 1, 1, 1, 0, %58;\n}\n"
            : "+f"(d[0]), "+f"(d[1]), "+f"(d[2]), "+f"(d[3]), "+f"(d[4]), "+f"(d[5]), "+f"(d[6]), "+f"(d[7]), "+f"(d[8]), "+f"(d[9]), "+f"(d[10]), "+f"(d[11]), "+f"(d[12]), "+f"(d[13]), "+f"(d[14]), "+f"(d[15]), "+f"(d[16]), "+f"(d[17]), "+f"(d[18]), "+f"(d[19]), "+f"(d[20]), "+f"(d[21]), "+f"(d[22]), "+f"(d[23]), "+f"(d[24]), "+f"(d[25]), "+f"(d[26]), "+f"(d[27]), "+f"(d[28]), "+f"(d[29]), "+f"(d[30]), "+f"(d[31]), "+f"(d[32]), "+f"(d[33]), "+f"(d[34]), "+f"(d[35]), "+f"(d[36]), "+f"(d[37]), "+f"(d[38]), "+f"(d[39]), "+f"(d[40]), "+f"(d[41]), "+f"(d[42]), "+f"(d[43]), "+f"(d[44]), "+f"(d[45]), "+f"(d[46]), "+f"(d[47]), "+f"(d[48]), "+f"(d[49]), "+f"(d[50]), "+f"(d[51]), "+f"(d[52]), "+f"(d[53]), "+f"(d[54]), "+f"(d[55])
            : "r"(alo), "r"(blo), "n"(TB), "n"(AHI), "n"(BHI));
    } else {
        asm volatile("{\n.reg .b64 da, db;\nmov.b64 da, {%56, %59};\nmov.b64 db, {%57, %60};\n"
            "wgmma.mma_async.sync.aligned.m64n112k16.f32.bf16.bf16 {%0, %1, %2, %3, %4, %5, %6, %7, %8, %9, %10, %11, %12, %13, %14, %15, %16, %17, %18, %19, %20, %21, %22, %23, %24, %25, %26, %27, %28, %29, %30, %31, %32, %33, %34, %35, %36, %37, %38, %39, %40, %41, %42, %43, %44, %45, %46, %47, %48, %49, %50, %51, %52, %53, %54, %55}, da, db, 0, 1, 1, 0, %58;\n}\n"
            : "=f"(d[0]), "=f"(d[1]), "=f"(d[2]), "=f"(d[3]), "=f"(d[4]), "=f"(d[5]), "=f"(d[6]), "=f"(d[7]), "=f"(d[8]), "=f"(d[9]), "=f"(d[10]), "=f"(d[11]), "=f"(d[12]), "=f"(d[13]), "=f"(d[14]), "=f"(d[15]), "=f"(d[16]), "=f"(d[17]), "=f"(d[18]), "=f"(d[19]), "=f"(d[20]), "=f"(d[21]), "=f"(d[22]), "=f"(d[23]), "=f"(d[24]), "=f"(d[25]), "=f"(d[26]), "=f"(d[27]), "=f"(d[28]), "=f"(d[29]), "=f"(d[30]), "=f"(d[31]), "=f"(d[32]), "=f"(d[33]), "=f"(d[34]), "=f"(d[35]), "=f"(d[36]), "=f"(d[37]), "=f"(d[38]), "=f"(d[39]), "=f"(d[40]), "=f"(d[41]), "=f"(d[42]), "=f"(d[43]), "=f"(d[44]), "=f"(d[45]), "=f"(d[46]), "=f"(d[47]), "=f"(d[48]), "=f"(d[49]), "=f"(d[50]), "=f"(d[51]), "=f"(d[52]), "=f"(d[53]), "=f"(d[54]), "=f"(d[55])
            : "r"(alo), "r"(blo), "n"(TB), "n"(AHI), "n"(BHI));
    }
}
template <int TB, uint32_t AHI, uint32_t BHI>
__device__ __forceinline__ void wgmma_n112_p(float (&d)[56], uint32_t alo, uint32_t blo, int acc) {
    asm volatile("{\n.reg .b64 da, db;\n.reg .pred p;\nsetp.ne.b32 p, %61, 0;\nmov.b64 da, {%56, %59};\nmov.b64 db, {%57, %60};\n"
        "wgmma.mma_async.sync.aligned.m64n112k16.f32.bf16.bf16 {%0, %1, %2, %3, %4, %5, %6, %7, %8, %9, %10, %11, %12, %13, %14, %15, %16, %17, %18, %19, %20, %21, %22, %23, %24, %25, %26, %27, %28, %29, %30, %31, %32, %33, %34, %35, %36, %37, %38, %39, %40, %41, %42, %43, %44, %45, %46, %47, %48, %49, %50, %51, %52, %53, %54, %55}, da, db, p, 1, 1, 0, %58;\n}\n"
        : "+f"(d[0]), "+f"(d[1]), "+f"(d[2]), "+f"(d[3]), "+f"(d[4]), "+f"(d[5]), "+f"(d[6]), "+f"(d[7]), "+f"(d[8]), "+f"(d[9]), "+f"(d[10]), "+f"(d[11]), "+f"(d[12]), "+f"(d[13]), "+f"(d[14]), "+f"(d[15]), "+f"(d[16]), "+f"(d[17]), "+f"(d[18]), "+f"(d[19]), "+f"(d[20]), "+f"(d[21]), "+f"(d[22]), "+f"(d[23]), "+f"(d[24]), "+f"(d[25]), "+f"(d[26]), "+f"(d[27]), "+f"(d[28]), "+f"(d[29]), "+f"(d[30]), "+f"(d[31]), "+f"(d[32]), "+f"(d[33]), "+f"(d[34]), "+f"(d[35]), "+f"(d[36]), "+f"(d[37]), "+f"(d[38]), "+f"(d[39]), "+f"(d[40]), "+f"(d[41]), "+f"(d[42]), "+f"(d[43]), "+f"(d[44]), "+f"(d[45]), "+f"(d[46]), "+f"(d[47]), "+f"(d[48]), "+f"(d[49]), "+f"(d[50]), "+f"(d[51]), "+f"(d[52]), "+f"(d[53]), "+f"(d[54]), "+f"(d[55])
        : "r"(alo), "r"(blo), "n"(TB), "n"(AHI), "n"(BHI), "r"(acc));
}
template <int TB, uint32_t AHI, uint32_t BHI>
__device__ __forceinline__ void wgmma_n168(float (&d)[84], uint32_t alo, uint32_t blo, bool acc) {
    if (acc) {
        asm volatile("{\n.reg .b64 da, db;\nmov.b64 da, {%84, %87};\nmov.b64 db, {%85, %88};\n"
            "wgmma.mma_async.sync.aligned.m64n168k16.f32.bf16.bf16 {%0, %1, %2, %3, %4, %5, %6, %7, %8, %9, %10, %11, %12, %13, %14, %15, %16, %17, %18, %19, %20, %21, %22, %23, %24, %25, %26, %27, %28, %29, %30, %31, %32, %33, %34, %35, %36, %37, %38, %39, %40, %41, %42, %43, %44, %45, %46, %47, %48, %49, %50, %51, %52, %53, %54, %55, %56, %57, %58, %59, %60, %61, %62, %63, %64, %65, %66, %67, %68, %69, %70, %71, %72, %73, %74, %75, %76, %77, %78, %79, %80, %81, %82, %83}, da, db, 1, 1, 1, 0, %86;\n}\n"
            : "+f"(d[0]), "+f"(d[1]), "+f"(d[2]), "+f"(d[3]), "+f"(d[4]), "+f"(d[5]), "+f"(d[6]), "+f"(d[7]), "+f"(d[8]), "+f"(d[9]), "+f"(d[10]), "+f"(d[11]), "+f"(d[12]), "+f"(d[13]), "+f"(d[14]), "+f"(d[15]), "+f"(d[16]), "+f"(d[17]), "+f"(d[18]), "+f"(d[19]), "+f"(d[20]), "+f"(d[21]), "+f"(d[22]), "+f"(d[23]), "+f"(d[24]), "+f"(d[25]), "+f"(d[26]), "+f"(d[27]), "+f"(d[28]), "+f"(d[29]), "+f"(d[30]), "+f"(d[31]), "+f"(d[32]), "+f"(d[33]), "+f"(d[34]), "+f"(d[35]), "+f"(d[36]), "+f"(d[37]), "+f"(d[38]), "+f"(d[39]), "+f"(d[40]), "+f"(d[41]), "+f"(d[42]), "+f"(d[43]), "+f"(d[44]), "+f"(d[45]), "+f"(d[46]), "+f"(d[47]), "+f"(d[48]), "+f"(d[49]), "+f"(d[50]), "+f"(d[51]), "+f"(d[52]), "+f"(d[53]), "+f"(d[54]), "+f"(d[55]), "+f"(d[56]), "+f"(d[57]), "+f"(d[58]), "+f"(d[59]), "+f"(d[60]), "+f"(d[61]), "+f"(d[62]), "+f"(d[63]), "+f"(d[64]), "+f"(d[65]), "+f"(d[66]), "+f"(d[67]), "+f"(d[68]), "+f"(d[69]), "+f"(d[70]), "+f"(d[71]), "+f"(d[72]), "+f"(d[73]), "+f"(d[74]), "+f"(d[75]), "+f"(d[76]), "+f"(d[77]), "+f"(d[78]), "+f"(d[79]), "+f"(d[80]), "+f"(d[81]), "+f"(d[82]), "+f"(d[83])
            : "r"(alo), "r"(blo), "n"(TB), "n"(AHI), "n"(BHI));
    } else {
        asm volatile("{\n.reg .b64 da, db;\nmov.b64 da, {%84, %87};\nmov.b64 db, {%85, %88};\n"
            "wgmma.mma_async.sync.aligned.m64n168k16.f32.bf16.bf16 {%0, %1, %2, %3, %4, %5, %6, %7, %8, %9, %10, %11, %12, %13, %14, %15, %16, %17, %18, %19, %20, %21, %22, %23, %24, %25, %26, %27, %28, %29, %30, %31, %32, %33, %34, %35, %36, %37, %38, %39, %40, %41, %42, %43, %44, %45, %46, %47, %48, %49, %50, %51, %52, %53, %54, %55, %56, %57, %58, %59, %60, %61, %62, %63, %64, %65, %66, %67, %68, %69, %70, %71, %72, %73, %74, %75, %76, %77, %78, %79, %80, %81, %82, %83}, da, db, 0, 1, 1, 0, %86;\n}\n"
            : "=f"(d[0]), "=f"(d[1]), "=f"(d[2]), "=f"(d[3]), "=f"(d[4]), "=f"(d[5]), "=f"(d[6]), "=f"(d[7]), "=f"(d[8]), "=f"(d[9]), "=f"(d[10]), "=f"(d[11]), "=f"(d[12]), "=f"(d[13]), "=f"(d[14]), "=f"(d[15]), "=f"(d[16]), "=f"(d[17]), "=f"(d[18]), "=f"(d[19]), "=f"(d[20]), "=f"(d[21]), "=f"(d[22]), "=f"(d[23]), "=f"(d[24]), "=f"(d[25]), "=f"(d[26]), "=f"(d[27]), "=f"(d[28]), "=f"(d[29]), "=f"(d[30]), "=f"(d[31]), "=f"(d[32]), "=f"(d[33]), "=f"(d[34]), "=f"(d[35]), "=f"(d[36]), "=f"(d[37]), "=f"(d[38]), "=f"(d[39]), "=f"(d[40]), "=f"(d[41]), "=f"(d[42]), "=f"(d[43]), "=f"(d[44]), "=f"(d[45]), "=f"(d[46]), "=f"(d[47]), "=f"(d[48]), "=f"(d[49]), "=f"(d[50]), "=f"(d[51]), "=f"(d[52]), "=f"(d[53]), "=f"(d[54]), "=f"(d[55]), "=f"(d[56]), "=f"(d[57]), "=f"(d[58]), "=f"(d[59]), "=f"(d[60]), "=f"(d[61]), "=f"(d[62]), "=f"(d[63]), "=f"(d[64]), "=f"(d[65]), "=f"(d[66]), "=f"(d[67]), "=f"(d[68]), "=f"(d[69]), "=f"(d[70]), "=f"(d[71]), "=f"(d[72]), "=f"(d[73]), "=f"(d[74]), "=f"(d[75]), "=f"(d[76]), "=f"(d[77]), "=f"(d[78]), "=f"(d[79]), "=f"(d[80]), "=f"(d[81]), "=f"(d[82]), "=f"(d[83])
            : "r"(alo), "r"(blo), "n"(TB), "n"(AHI), "n"(BHI));
    }
}
template <int TB, uint32_t AHI, uint32_t BHI>
__device__ __forceinline__ void wgmma_n168_p(float (&d)[84], uint32_t alo, uint32_t blo, int acc) {
    asm volatile("{\n.reg .b64 da, db;\n.reg .pred p;\nsetp.ne.b32 p, %89, 0;\nmov.b64 da, {%84, %87};\nmov.b64 db, {%85, %88};\n"
        "wgmma.mma_async.sync.aligned.m64n168k16.f32.bf16.bf16 {%0, %1, %2, %3, %4, %5, %6, %7, %8, %9, %10, %11, %12, %13, %14, %15, %16, %17, %18, %19, %20, %21, %22, %23, %24, %25, %26, %27, %28, %29, %30, %31, %32, %33, %34, %35, %36, %37, %38, %39, %40, %41, %42, %43, %44, %45, %46, %47, %48, %49, %50, %51, %52, %53, %54, %55, %56, %57, %58, %59, %60, %61, %62, %63, %64, %65, %66, %67, %68, %69, %70, %71, %72, %73, %74, %75, %76, %77, %78, %79, %80, %81, %82, %83}, da, db, p, 1, 1, 0, %86;\n}\n"
        : "+f"(d[0]), "+f"(d[1]), "+f"(d[2]), "+f"(d[3]), "+f"(d[4]), "+f"(d[5]), "+f"(d[6]), "+f"(d[7]), "+f"(d[8]), "+f"(d[9]), "+f"(d[10]), "+f"(d[11]), "+f"(d[12]), "+f"(d[13]), "+f"(d[14]), "+f"(d[15]), "+f"(d[16]), "+f"(d[17]), "+f"(d[18]), "+f"(d[19]), "+f"(d[20]), "+f"(d[21]), "+f"(d[22]), "+f"(d[23]), "+f"(d[24]), "+f"(d[25]), "+f"(d[26]), "+f"(d[27]), "+f"(d[28]), "+f"(d[29]), "+f"(d[30]), "+f"(d[31]), "+f"(d[32]), "+f"(d[33]), "+f"(d[34]), "+f"(d[35]), "+f"(d[36]), "+f"(d[37]), "+f"(d[38]), "+f"(d[39]), "+f"(d[40]), "+f"(d[41]), "+f"(d[42]), "+f"(d[43]), "+f"(d[44]), "+f"(d[45]), "+f"(d[46]), "+f"(d[47]), "+f"(d[48]), "+f"(d[49]), "+f"(d[50]), "+f"(d[51]), "+f"(d[52]), "+f"(d[53]), "+f"(d[54]), "+f"(d[55]), "+f"(d[56]), "+f"(d[57]), "+f"(d[58]), "+f"(d[59]), "+f"(d[60]), "+f"(d[61]), "+f"(d[62]), "+f"(d[63]), "+f"(d[64]), "+f"(d[65]), "+f"(d[66]), "+f"(d[67]), "+f"(d[68]), "+f"(d[69]), "+f"(d[70]), "+f"(d[71]), "+f"(d[72]), "+f"(d[73]), "+f"(d[74]), "+f"(d[75]), "+f"(d[76]), "+f"(d[77]), "+f"(d[78]), "+f"(d[79]), "+f"(d[80]), "+f"(d[81]), "+f"(d[82]), "+f"(d[83])
        : "r"(alo), "r"(blo), "n"(TB), "n"(AHI), "n"(BHI), "r"(acc));
}

struct Params {
    CUtensorMap tm_x;
    CUtensorMap tm_win;
    CUtensorMap tm_wqkv;
    CUtensorMap tm_wsp;
    CUtensorMap tm_wo;
    CUtensorMap tm_wout;
    const bf16* x;
    const bf16* wqkv;
    const bf16* wo;
    const bf16* win;
    const bf16* wsp;
    const bf16* bsp;
    const bf16* wout;
    bf16* out;
};

__device__ __forceinline__ uint32_t greg(int pos) { return ((GORDER >> (4 * pos)) & 7u) * GSTRIDE; }

__device__ __forceinline__ float quad_sum(float v) {
    v += __shfl_xor_sync(0xffffffffu, v, 1);
    v += __shfl_xor_sync(0xffffffffu, v, 2);
    return v;
}

constexpr uint64_t CA_P = 0x423502505143ull;
constexpr uint64_t CW_P = 0x32dc987610dcull;

__global__ void __cluster_dims__(2, 1, 1) __launch_bounds__(384, 1)
fused_kernel(const __grid_constant__ Params P) {
    extern __shared__ __align__(1024) uint8_t smem_raw[];
    const uint32_t sb = (smem_u32(smem_raw) + 1023u) & ~1023u;
    const uint32_t bars = sb + BAR_OFF;
    const int h = blockIdx.x & 1;
    const int pr = blockIdx.x >> 1;
    const int i = pr & 15, jj = pr >> 4, j = 2 * jj + h;
    const int lane = threadIdx.x & 31, g = lane >> 2, t = lane & 3;
    const int warp = __shfl_sync(0xffffffffu, threadIdx.x >> 5, 0);

    if (warp < 8) {
        const int wg = warp >> 2, w = warp & 3;
        const bool sig = (lane == 0) && (w == 0);
        const bool sig2 = (lane == 0) && (w < 2);
        uint32_t rbars;
        asm volatile("mapa.shared::cluster.u32 %0, %1, %2;" : "=r"(rbars) : "r"(bars), "r"(h ^ (w & 1)));
        float rs0, rs1;
        cluster_arrive_relaxed();
        asm volatile("setmaxnreg.inc.sync.aligned.u32 200;");
        bar_sync(9, 384);
        if (threadIdx.x == 0) TS(53);
        {
            uint4 xa[14], xb[14];
            const int pg = (g >> 1) | ((g & 1) << 2);
            const uint32_t rowaddr = sb + XN_OFF + (warp * 16 + pg) * 128;
            const uint32_t sw0 = (t ^ pg) << 4, sw1 = ((4 | t) ^ pg) << 4;
            float sA[4] = {0.f, 0.f, 0.f, 0.f}, sB[4] = {0.f, 0.f, 0.f, 0.f}, qA[4] = {0.f, 0.f, 0.f, 0.f}, qB[4] = {0.f, 0.f, 0.f, 0.f};
            float qC[4] = {0.f, 0.f, 0.f, 0.f}, qD[4] = {0.f, 0.f, 0.f, 0.f};
            const uint32_t ONES = 0x3F803F80u;
#pragma unroll
            for (int c = 0; c < 14; c++) {
                if ((c & 1) == 0) {
                    mbar_wait(bars + 8 * (B_FULLX + (c >> 1)));
                    if (c == 0 && threadIdx.x == 0) TS(56);
                    const uint32_t a = rowaddr + (c >> 1) * 16384;
                    xa[c] = lds_v4(a + sw0); xb[c] = lds_v4(a + sw0 + 1024);
                    xa[c + 1] = lds_v4(a + sw1); xb[c + 1] = lds_v4(a + sw1 + 1024);
                }
                mma16816(sA, xa[c].x, xa[c].y, xa[c].z, xa[c].w, ONES, ONES);
                mma16816(sB, xb[c].x, xb[c].y, xb[c].z, xb[c].w, ONES, ONES);
                mma1688(qA, xa[c].x, xa[c].y, xa[c].x); mma1688(qB, xa[c].x, xa[c].y, xa[c].y);
                mma1688(qC, xb[c].x, xb[c].y, xb[c].x); mma1688(qD, xb[c].x, xb[c].y, xb[c].y);
                mma1688(qA, xa[c].z, xa[c].w, xa[c].z); mma1688(qB, xa[c].z, xa[c].w, xa[c].w);
                mma1688(qC, xb[c].z, xb[c].w, xb[c].z); mma1688(qD, xb[c].z, xb[c].w, xb[c].w);
            }
            const float ma = (sA[0] + sA[2]) * (1.0f / 448.0f), mb = (sB[0] + sB[2]) * (1.0f / 448.0f);
            const uint32_t ma2 = pack_bf16(ma, ma), mb2 = pack_bf16(mb, mb);
#pragma unroll
            for (int c = 0; c < 14; c++) {
                xa[c].x = sub_bf16x2(xa[c].x, ma2); xa[c].y = sub_bf16x2(xa[c].y, ma2);
                xa[c].z = sub_bf16x2(xa[c].z, ma2); xa[c].w = sub_bf16x2(xa[c].w, ma2);
                xb[c].x = sub_bf16x2(xb[c].x, mb2); xb[c].y = sub_bf16x2(xb[c].y, mb2);
                xb[c].z = sub_bf16x2(xb[c].z, mb2); xb[c].w = sub_bf16x2(xb[c].w, mb2);
                const uint32_t a = rowaddr + (c >> 1) * 16384 + ((c & 1) ? sw1 : sw0);
                sts_v4(a, xa[c]);
                sts_v4(a + 1024, xb[c]);
            }
            fence_async_smem();
            const float qa = (g & 1) ? qA[1] + qB[3] : qA[0] + qB[2];
            const float qb = (g & 1) ? qC[1] + qD[3] : qC[0] + qD[2];
            const float ra = rsqrtf(fmaxf(qa * (1.0f / 448.0f) - ma * ma, 0.f) + 1e-5f);
            const float rb = rsqrtf(fmaxf(qb * (1.0f / 448.0f) - mb * mb, 0.f) + 1e-5f);
            const int gs = ((g & 3) << 1) | (g >> 2);
            rs0 = __shfl_sync(0xffffffffu, ra, gs * 4 + (gs >> 1));
            rs1 = __shfl_sync(0xffffffffu, rb, gs * 4 + (gs >> 1));
        }
        if (threadIdx.x == 0) TS(58);
        bar_sync(1 + wg, 128);
        if (threadIdx.x == 0) TS(0);
        unsigned epoch;
        asm volatile("ld.relaxed.gpu.global.u32 %0, [%1];" : "=r"(epoch) : "l"(&g_done) : "memory");

        const GeluC G0 = gelu_consts(rs0), G1 = gelu_consts(rs1);
        const uint32_t dA_xn = dlo(sb + XN_OFF + wg * 8192, 16);
        const uint32_t dB_ra = dlo(sb + RINGA_OFF, 8192);
        float acc_a[56], acc_b[56], acc_c[84];
        {
            int slot = 1;
#pragma unroll 1
            for (int kb = 0; kb < 7; kb++) {
                mbar_wait(bars + 8 * (B_FULLA + kb));
                if (threadIdx.x == 0 && kb == 0) TS(14);
                if (threadIdx.x == 0 && kb == 5) TS(15);
                wgmma_fence();
                const uint32_t da = dA_xn + kb * 1024, db = dB_ra + slot * 1024;
                wgmma_n112_p<1, HI_SW128, HI_SW128>(acc_a, da, db, kb);
#pragma unroll
                for (int k = 1; k < 4; k++) wgmma_n112<1, HI_SW128, HI_SW128>(acc_a, da + k * 2, db + k * 128, true);
                wgmma_commit();
                wgmma_wait<1>();
                if (sig && kb > 0) mbar_arrive(bars + 8 * (B_DONEA + kb - 1));
                slot = slot == 4 ? 0 : slot + 1;
            }
        }
        cluster_wait();
        epoch >>= 7;
        const uint32_t tag = (epoch % 3u) + 1u;
        {
            float s0 = 0.f, q0 = 0.f, s1 = 0.f, q1 = 0.f;
            uint4 p0, p1;
            const uint4* sp = g_stats + ((i * 8 + 2 * t) * 64 + warp * 8 + g);
#pragma unroll
            for (int kb = 0; kb < 7; kb++) {
                mbar_wait(bars + 8 * (B_FULLA + 7 + kb));
                wgmma_fence();
#pragma unroll
                for (int k = 0; k < 4; k++)
                    wgmma_n112<1, HI_SW128, HI_SW128>(acc_b, dA_xn + kb * 1024 + k * 2, dB_ra + ((kb + 8) % 5) * 1024 + k * 128, (kb | k) != 0);
                wgmma_commit();
                wgmma_wait<1>();
                if (sig) mbar_arrive(bars + 8 * (B_DONEA + 6 + kb));
                if (kb == 0) { reg_fence(acc_a); if (threadIdx.x == 0) TS(1); }
                if (kb < 3) {
#pragma unroll
                    for (int b = kb * 5; b < (kb == 2 ? 14 : kb * 5 + 5); b++) {
                        float v0 = gelu_s(acc_a[4 * b], G0), v1 = gelu_s(acc_a[4 * b + 1], G0);
                        float v2 = gelu_s(acc_a[4 * b + 2], G1), v3 = gelu_s(acc_a[4 * b + 3], G1);
                        s0 += v0 + v1; q0 = fmaf(v0, v0, fmaf(v1, v1, q0));
                        s1 += v2 + v3; q1 = fmaf(v2, v2, fmaf(v3, v3, q1));
                        acc_a[4 * b] = v0; acc_a[4 * b + 1] = v1; acc_a[4 * b + 2] = v2; acc_a[4 * b + 3] = v3;
                    }
                }
                if (kb == 2) {
                    s0 = quad_sum(s0); q0 = quad_sum(q0); s1 = quad_sum(s1); q1 = quad_sum(q1);
                    if (t == 0) {
                        uint4 pk;
                        pk.x = (__float_as_uint(s0) & ~3u) | tag; pk.y = (__float_as_uint(q0) & ~3u) | tag;
                        pk.z = (__float_as_uint(s1) & ~3u) | tag; pk.w = (__float_as_uint(q1) & ~3u) | tag;
                        st_relaxed_v4(g_stats + ((i * 8 + j) * 64 + warp * 8 + g), pk);
                    }
                    if (threadIdx.x == 0) TS(2);
                }
                if (kb == 4) { p0 = ld_relaxed_v4(sp); p1 = ld_relaxed_v4(sp + 64); }
                if (kb == 5) {
                    uint32_t n = 0;
                    while (true) {
                        const uint32_t all = p0.x & p0.y & p0.z & p0.w & p1.x & p1.y & p1.z & p1.w & 3u;
                        const uint32_t any = (p0.x | p0.y | p0.z | p0.w | p1.x | p1.y | p1.z | p1.w) & 3u;
                        if (__all_sync(0xffffffffu, all == tag && any == tag)) break;
                        SPIN_CHECK(n, 1000)
                        p0 = ld_relaxed_v4(sp); p1 = ld_relaxed_v4(sp + 64);
                    }
                    if (threadIdx.x == 0) TS(3);
                    const float m0 = quad_sum(__uint_as_float(p0.x) + __uint_as_float(p1.x)) * (1.0f / 896.0f);
                    const float Q0 = quad_sum(__uint_as_float(p0.y) + __uint_as_float(p1.y));
                    const float m1 = quad_sum(__uint_as_float(p0.z) + __uint_as_float(p1.z)) * (1.0f / 896.0f);
                    const float Q1 = quad_sum(__uint_as_float(p0.w) + __uint_as_float(p1.w));
                    const float r0 = rsqrtf(fmaxf(Q0 * (1.0f / 896.0f) - m0 * m0, 0.f) + 1e-5f);
                    const float r1 = rsqrtf(fmaxf(Q1 * (1.0f / 896.0f) - m1 * m1, 0.f) + 1e-5f);
                    const float n0 = -m0 * r0, n1 = -m1 * r1;
                    const int m = lane >> 3;
                    const uint32_t sa = sb + Z2S_OFF + (warp * 2 + (m & 1)) * 1792 + ((m >> 1) * 8 + (lane & 7)) * 16;
#pragma unroll
                    for (int b = 0; b < 14; b += 2) {
                        stmat_x4_t(sa + b * 128,
                                   pack_bf16(fmaf(acc_a[4 * b], r0, n0), fmaf(acc_a[4 * b + 1], r0, n0)),
                                   pack_bf16(fmaf(acc_a[4 * b + 2], r1, n1), fmaf(acc_a[4 * b + 3], r1, n1)),
                                   pack_bf16(fmaf(acc_a[4 * b + 4], r0, n0), fmaf(acc_a[4 * b + 5], r0, n0)),
                                   pack_bf16(fmaf(acc_a[4 * b + 6], r1, n1), fmaf(acc_a[4 * b + 7], r1, n1)));
                    }
                    fence_async_smem();
                    bar_arrive(3 + wg, 160);
                    if (threadIdx.x == 0) TS(4);
                }
            }
        }
        uint32_t z1p[28];
#pragma unroll
        for (int kb = 0; kb < 7; kb++) {
            mbar_wait(bars + 8 * (B_FULLA + 14 + kb));
            wgmma_fence();
#pragma unroll
            for (int k = 0; k < 4; k++)
                wgmma_n168<1, HI_SW128, HI_SW128>(acc_c, dA_xn + kb * 1024 + k * 2, dB_ra + (kb % 3) * 1536 + k * 128, (kb | k) != 0);
            wgmma_commit();
            wgmma_wait<1>();
            if (kb == 0) { if (sig) mbar_arrive(bars + 8 * (B_DONEA + 13)); }
            else if (sig2) mbar_arrive_cl(rbars + 8 * (B_DONEA + 13 + kb));
            if (kb == 0) { reg_fence(acc_b); if (threadIdx.x == 0) TS(5); }
#pragma unroll
            for (int b = 2 * kb; b < 2 * kb + 2; b++) {
                z1p[2 * b] = pack_bf16(gelu_s(acc_b[4 * b], G0), gelu_s(acc_b[4 * b + 1], G0));
                z1p[2 * b + 1] = pack_bf16(gelu_s(acc_b[4 * b + 2], G1), gelu_s(acc_b[4 * b + 3], G1));
            }
        }
        const uint32_t dA_g = dlo(sb + wg * 8192, 16);
        const uint32_t dB_g = dlo(sb + 16384, 1792);
        const int row0 = i * 128 + warp * 16 + g;
#pragma unroll
        for (int kb = 0; kb < 2; kb++) {
            mbar_wait(bars + 8 * (B_FULLB + kb));
            if (kb == 0 && threadIdx.x == 0) TS(6);
            wgmma_fence();
#pragma unroll
            for (int k = 0; k < 4; k++)
                wgmma_n112<0, HI_SW128, HI_NOSW>(acc_a, dA_g + kb * (GSTRIDE >> 4) + k * 2, dB_g + kb * (GSTRIDE >> 4) + k * 224, (kb | k) != 0);
            wgmma_commit();
            wgmma_wait<1>();
            if (sig2) mbar_arrive_cl(rbars + 8 * (kb == 0 ? B_DONEA + 20 : B_DONEB + kb - 1));
            if (kb == 0) { reg_fence(acc_c); if (threadIdx.x == 0) TS(7); }
            uint8_t* qp = g_qkv + ((size_t)((21 * j * 2 + (g & 1)) * 1024 + (row0 >> 1))) * 16 + t * 4;
#pragma unroll
            for (int b = 11 * kb; b < (kb == 0 ? 11 : 21); b++) {
                *reinterpret_cast<uint32_t*>(qp + b * 32768) = pack_bf16(acc_c[4 * b] * rs0, acc_c[4 * b + 1] * rs0);
                *reinterpret_cast<uint32_t*>(qp + b * 32768 + 64) = pack_bf16(acc_c[4 * b + 2] * rs1, acc_c[4 * b + 3] * rs1);
            }
            if (kb == 1) bar_arrive(5 + wg, 160);
        }
        {
            int pos = 2;
#pragma unroll 1
            for (int kb = 2; kb < 32; kb++) {
                const uint32_t ro = greg(pos) >> 4;
                pos = pos == 6 ? 0 : pos + 1;
                mbar_wait(bars + 8 * (B_FULLB + kb));
                wgmma_fence();
#pragma unroll
                for (int k = 0; k < 4; k++) wgmma_n112<0, HI_SW128, HI_NOSW>(acc_a, dA_g + ro + k * 2, dB_g + ro + k * 224, true);
                wgmma_commit();
                wgmma_wait<1>();
                if (sig2) mbar_arrive_cl(rbars + 8 * (B_DONEB + kb - 1));
            }
        }
        if (threadIdx.x == 0) TS(13);
        float acc3[28];
        const uint32_t dA_c = dlo(sb + wg * GRAN, 1024);
        const uint32_t dB_c = dlo(sb, 8192);
        const float b0 = __bfloat162float(P.bsp[row0]), b1 = __bfloat162float(P.bsp[row0 + 8]);
        uint32_t xr[14];
        {
            const bf16* xp = P.x + (size_t)row0 * 448 + j * 56 + 2 * t;
#pragma unroll
            for (int b = 0; b < 7; b++) {
                xr[2 * b] = __ldg(reinterpret_cast<const uint32_t*>(xp + 8 * b));
                xr[2 * b + 1] = __ldg(reinterpret_cast<const uint32_t*>(xp + 8 * b + 8 * 448));
            }
        }
        {
            mbar_wait(bars + 8 * (B_FULLCW + 0));
            mbar_wait(bars + 8 * (B_FULLCA + wg));
            if (threadIdx.x == 0) TS(16);
            wgmma_fence();
#pragma unroll
            for (int k = 0; k < 7; k++)
                wgmma_n56<1, HI_NOSW, HI_SW128>(acc3, dA_c + 3 * (GSTRIDE >> 4) + k * 128, dB_c + 6 * (GSTRIDE >> 4) + k * 128, k != 0);
            wgmma_commit();
            wgmma_wait<1>();
            if (sig2) mbar_arrive_cl(rbars + 8 * (B_DONEB + 31));
            reg_fence(acc_a);
            if (threadIdx.x == 0) TS(8);
            mbar_wait(bars + 8 * (B_DONEB + 30));
            const int m = lane >> 3;
            const uint32_t sa = sb + 2 * GSTRIDE + wg * GRAN + (m >> 1) * 1024 + (w * 16 + (m & 1) * 8 + (lane & 7)) * 16;
#pragma unroll
            for (int b = 0; b < 14; b += 2) {
                stmat_x4(sa + b * 1024,
                         pack_bf16((acc_a[4 * b] + b0) * bf_lo(z1p[2 * b]), (acc_a[4 * b + 1] + b0) * bf_hi(z1p[2 * b])),
                         pack_bf16((acc_a[4 * b + 2] + b1) * bf_lo(z1p[2 * b + 1]), (acc_a[4 * b + 3] + b1) * bf_hi(z1p[2 * b + 1])),
                         pack_bf16((acc_a[4 * b + 4] + b0) * bf_lo(z1p[2 * b + 2]), (acc_a[4 * b + 5] + b0) * bf_hi(z1p[2 * b + 2])),
                         pack_bf16((acc_a[4 * b + 6] + b1) * bf_lo(z1p[2 * b + 3]), (acc_a[4 * b + 7] + b1) * bf_hi(z1p[2 * b + 3])));
            }
            fence_async_smem();
            bar_arrive(7 + wg, 160);
            if (threadIdx.x == 0) TS(9);
            wgmma_wait<0>();
            if (sig2) mbar_arrive_cl(rbars + 8 * (B_DONEC + 0));
        }
#pragma unroll 1
        for (int n = 1; n < 12; n++) {
            const uint32_t ca = (uint32_t)(CA_P >> (4 * n)) & 7u, cw = (uint32_t)(CW_P >> (4 * n)) & 15u;
            const uint32_t da = dA_c + ca * (GSTRIDE >> 4), db = dB_c + (cw >> 1) * (GSTRIDE >> 4) + (cw & 1) * (GRAN >> 4);
            mbar_wait(bars + 8 * (B_FULLCW + n));
            mbar_wait(bars + 8 * (B_FULLCA + 2 * n + wg));
            if (threadIdx.x == 0) TS(16 + n);
            wgmma_fence();
#pragma unroll
            for (int k = 0; k < 7; k++) wgmma_n56<1, HI_NOSW, HI_SW128>(acc3, da + k * 128, db + k * 128, true);
            wgmma_commit();
            wgmma_wait<0>();
            if (sig2) mbar_arrive_cl(rbars + 8 * (B_DONEC + n));
        }
        reg_fence(acc3);
        if (threadIdx.x == 0) TS(10);
        {
            bf16* op = P.out + (size_t)row0 * 448 + j * 56 + 2 * t;
#pragma unroll
            for (int b = 0; b < 7; b++) {
                *reinterpret_cast<uint32_t*>(op + 8 * b) = pack_bf16(acc3[4 * b] + bf_lo(xr[2 * b]), acc3[4 * b + 1] + bf_hi(xr[2 * b]));
                *reinterpret_cast<uint32_t*>(op + 8 * b + 8 * 448) = pack_bf16(acc3[4 * b + 2] + bf_lo(xr[2 * b + 1]), acc3[4 * b + 3] + bf_hi(xr[2 * b + 1]));
            }
        }
        if (threadIdx.x == 0) TS(11);
        cluster_arrive_relaxed();
        cluster_wait();
        if (threadIdx.x == 0) { atomicAdd(&g_done, 1u); TS(12); }
    } else {
        {
            const int tid = threadIdx.x - 256;
#pragma unroll 1
            for (int b = tid; b < NBARS; b += 128) {
                uint32_t cnt = 4, tx = 0;
                if (b < B_DONEA) tx = b < 14 ? 16384 : 24576;
                else if (b < B_DONEA + 14) cnt = 2;
                else if (b >= B_FULLB && b < B_DONEB) tx = 30720;
                else if (b >= B_FULLCW && b < B_DONEC) tx = GRAN;
                else if (b >= B_FULLX) tx = 16384;
                mbar_init(bars + 8 * b, tx ? 1u : cnt);
                if (tx) mbar_expect_tx(bars + 8 * b, tx);
            }
            asm volatile("fence.mbarrier_init.release.cluster;" ::: "memory");
            asm volatile("setmaxnreg.dec.sync.aligned.u32 104;");
            bar_sync(9, 384);
            if (threadIdx.x == 256) TS(60);
            cluster_arrive_relaxed();
        }
        if (warp == 8) {
            if (lane == 0) {
#pragma unroll 1
                for (int kb = 0; kb < 7; kb++) tma_2d(sb + XN_OFF + kb * 16384, &P.tm_x, kb * 64, i * 128, bars + 8 * (B_FULLX + kb));
                int slot = 1;
#pragma unroll 1
                for (int n = 0; n < 14; n++) {
                    if (n >= 5) mbar_wait(bars + 8 * (B_DONEA + n - 5));
                    const uint32_t dst = sb + RINGA_OFF + slot * 16384;
                    slot = slot == 4 ? 0 : slot + 1;
                    const int grp = n < 7 ? 8 + j : j, kb = n < 7 ? n : n - 7;
                    tma_3d(dst, &P.tm_win, 0, grp, kb * 64, bars + 8 * (B_FULLA + n));
                    tma_3d(dst + 8192, &P.tm_win, 64, grp, kb * 64, bars + 8 * (B_FULLA + n));
                }
            }
            __syncwarp();
            cluster_wait();
            if (lane == 0) {
                constexpr uint64_t DEP = 0xAA99977655431ull << 4;
                int m = 0, kb = 0, pos = 0, s3 = 0;
#pragma unroll 1
                for (int k = 0; k < 39; k++) {
                    mbar_wait(bars + 8 * (k < 14 ? B_DONEA + 10 + (int)((DEP >> (4 * k)) & 15u) : B_DONEB + k - 14));
                    if (k < 8 && k != 5) {
                        const uint32_t dst = sb + RINGA_OFF + s3 * 24576;
                        s3 = s3 == 2 ? 0 : s3 + 1;
#pragma unroll 1
                        for (int c = 0; c < 3; c++) tma_3d(dst + c * 8192, &P.tm_wqkv, c * 64, j, m * 64, bars + 8 * (B_FULLA + 14 + m));
                        m++;
                    } else {
                        if (kb == 4) mbar_wait(bars + 8 * B_Z2SFREE);
                        tma_2d_mc(sb + greg(pos) + h * 8192, &P.tm_wsp, kb * 64, i * 128 + h * 64, bars + 8 * (B_FULLB + kb));
                        pos = pos == 6 ? 0 : pos + 1;
                        kb++;
                    }
                }
#pragma unroll 1
                for (int n = 0; n < 12; n++) {
                    const int dep = n < 2 ? B_DONEB + 25 : n < 4 ? B_DONEB + 28 : n < 6 ? B_DONEC : n < 10 ? B_DONEC + 1 : B_DONEC + 2;
                    mbar_wait(bars + 8 * dep);
                    const uint32_t cw = (uint32_t)(CW_P >> (4 * n)) & 15u;
                    tma_3d(sb + (cw >> 1) * GSTRIDE + (cw & 1) * GRAN, n < 4 ? &P.tm_wo : &P.tm_wout, 0, j,
                           (n < 4 ? n : ((2 * jj + n - 4) & 7)) * 112, bars + 8 * (B_FULLCW + n));
                }
            }
        } else if (warp == 9) {
            cluster_wait();
            const unsigned tgt = (ld_relaxed(&g_done) >> 7) + 1u;
            {
                unsigned ready = 0;
                int pos = 0;
#pragma unroll 1
                for (int kb = 0; kb < 32; kb++) {
                    uint32_t n = 0;
                    while (!((ready >> kb) & 1u)) {
                        ready = __ballot_sync(0xffffffffu, ld_acquire(g_z2flag + j * 32 + lane) == tgt);
                        SPIN_CHECK(n, 1100 + kb)
                        fence_async_global();
                    }
                    if (lane == 0) {
                        if (kb == 0) TS(32);
                        mbar_wait(bars + 8 * (kb >= 7 ? B_DONEB + kb - 7 : B_DONEA + 10 + (int)((0xAA99975u >> (4 * kb)) & 15u)));
                        if (kb == 4) mbar_wait(bars + 8 * B_Z2SFREE);
                        bulk_load(sb + greg(pos) + 16384, g_z2t + (size_t)((kb >> 1) * 8 + j) * 28672 + (kb & 1) * GRAN, GRAN, bars + 8 * (B_FULLB + kb));
                    }
                    pos = pos == 6 ? 0 : pos + 1;
                    __syncwarp();
                }
            }
            {
                unsigned ready = 0;
                const uint8_t* src = g_ou + (size_t)(i * 2 + h) * 168 * 1024;
                constexpr uint64_t DEPA = 0x76554D335310ull;
#pragma unroll 1
                for (int n = 0; n < 12; n++) {
                    const int jt = (2 * jj + n - 4) & 7;
                    const unsigned need = n < 4 ? (3u << (8 + 2 * n)) : (1u << jt);
                    uint32_t cnt = 0;
                    while ((ready & need) != need) {
                        ready = __ballot_sync(0xffffffffu, ld_acquire(g_ouflag + (i * 2 + h) * 16 + (lane & 15)) == tgt);
                        SPIN_CHECK(cnt, 1200 + n)
                        fence_async_global();
                    }
                    if (lane == 0) {
                        TS(33 + n);
                        mbar_wait(bars + 8 * ((n < 4 ? B_DONEB + 26 : B_DONEC) + (int)((DEPA >> (4 * n)) & 15u)));
                        const uint32_t reg = (uint32_t)(CA_P >> (4 * n)) & 7u;
                        bulk_load_mc(sb + reg * GSTRIDE + h * GRAN, src + (size_t)(n < 4 ? n : 4 + jt) * GRAN, GRAN, bars + 8 * (B_FULLCA + 2 * n + h));
                    }
                    __syncwarp();
                }
            }
        } else {
            const int a = warp - 10;
            const int hb = i * 2 + a;
            if (a == 0) {
                if (lane == 0) l2_prefetch(reinterpret_cast<const uint8_t*>(P.win) + (size_t)blockIdx.x * 12544, 12544);
                if (lane == 1) l2_prefetch(reinterpret_cast<const uint8_t*>(P.wqkv) + (size_t)blockIdx.x * 9408, 9408);
            }
            cluster_wait();
            __nanosleep(1000);
            l2_prefetch(reinterpret_cast<const uint8_t*>(P.wsp) + (size_t)blockIdx.x * 65536 + (a * 32 + lane) * 1024, 1024);
            if (a == 1) {
                if (lane == 0) l2_prefetch(reinterpret_cast<const uint8_t*>(P.wo) + (size_t)blockIdx.x * 3136, 3136);
                if (lane == 1) l2_prefetch(reinterpret_cast<const uint8_t*>(P.wout) + (size_t)blockIdx.x * 6272, 6272);
            }
            const unsigned tgt = (ld_relaxed(&g_done) >> 7) + 1u;
            bar_sync(3 + a, 160);
            if (lane == 0) {
                bulk_store(g_z2t + (size_t)(i * 8 + j) * 28672 + a * GRAN, sb + Z2S_OFF + a * GRAN, GRAN);
                asm volatile("cp.async.bulk.wait_group.read 0;" ::: "memory");
                mbar_arrive(bars + 8 * B_Z2SFREE);
                mbar_arrive_remote(bars + 8 * B_Z2SFREE, h ^ 1);
                asm volatile("cp.async.bulk.wait_group 0;" ::: "memory");
                fence_async_global();
                st_release(g_z2flag + j * 32 + hb, tgt);
                if (a == 0) TS(48);
            }
            __syncwarp();
            bar_sync(5 + a, 160);
            if (lane == 0) { st_release(g_qflag + hb * 8 + j, tgt); if (a == 0) TS(49); }
            __syncwarp();
            {
                const int fi = hb > 0 ? (hb - 1) * 8 + (lane & 15) : (lane & 7);
                uint32_t n = 0;
                while (!__all_sync(0xffffffffu, ld_acquire(g_qflag + fi) == tgt)) { SPIN_CHECK(n, 1300) }
            }
            if (lane == 0 && a == 0) TS(50);
#pragma unroll 1
            for (int task = 0; task < 4; task++) {
                const int e = task & 1, p = task >> 1;
                const int c = 7 * j + 3 * e + t;
                const uint8_t* base = g_qkv + (size_t)((c * 2 + p) * 1024 + hb * 32 + g) * 16;
                uint4 qq[4], kk[5], vv[5];
#pragma unroll
                for (int n = 0; n < 5; n++) {
                    const int off = (n == 0 && hb == 0) ? 0 : (n - 1) * 128;
                    kk[n] = ld_v4(base + (size_t)56 * 32768 + off);
                    if (n < 4) qq[n] = ld_v4(base + n * 128);
                }
#pragma unroll
                for (int n = 0; n < 5; n++) {
                    const int off = (n == 0 && hb == 0) ? 0 : (n - 1) * 128;
                    vv[n] = ld_v4(base + (size_t)112 * 32768 + off);
                }
                const bool zhi = (e == 0 && t == 3), zlo = (e == 1 && t == 0);
                const bool c0 = 2 * t > g, c1 = 2 * t + 1 > g;
#pragma unroll
                for (int blk = 0; blk < 2; blk++) {
                    uint4 qa = qq[2 * blk], qb = qq[2 * blk + 1];
                    if (zhi) { qa.z = qa.w = qb.z = qb.w = 0u; }
                    if (zlo) { qa.x = qa.y = qb.x = qb.y = 0u; }
                    float s[3][4];
#pragma unroll
                    for (int n = 0; n < 3; n++) {
                        s[n][0] = s[n][1] = s[n][2] = s[n][3] = 0.f;
                        mma16816(s[n], qa.x, qb.x, qa.y, qb.y, kk[2 * blk + n].x, kk[2 * blk + n].y);
                        mma16816(s[n], qa.z, qb.z, qa.w, qb.w, kk[2 * blk + n].z, kk[2 * blk + n].w);
                    }
                    const float NEG = -3.0e38f;
                    const bool first = (blk == 0 && hb == 0);
                    float l0[4], l1[4];
                    l0[0] = (c0 && !first) ? s[0][0] : NEG;
                    l0[1] = (c1 && !first) ? s[0][1] : NEG;
                    l0[2] = !c0 ? s[1][0] : NEG;
                    l0[3] = !c1 ? s[1][1] : NEG;
                    l1[0] = c0 ? s[1][2] : NEG;
                    l1[1] = c1 ? s[1][3] : NEG;
                    l1[2] = !c0 ? s[2][2] : NEG;
                    l1[3] = !c1 ? s[2][3] : NEG;
                    float m0 = fmaxf(fmaxf(l0[0], l0[1]), fmaxf(l0[2], l0[3]));
                    float m1 = fmaxf(fmaxf(l1[0], l1[1]), fmaxf(l1[2], l1[3]));
                    m0 = fmaxf(m0, __shfl_xor_sync(0xffffffffu, m0, 1)); m1 = fmaxf(m1, __shfl_xor_sync(0xffffffffu, m1, 1));
                    m0 = fmaxf(m0, __shfl_xor_sync(0xffffffffu, m0, 2)); m1 = fmaxf(m1, __shfl_xor_sync(0xffffffffu, m1, 2));
                    const float sc = 0.18898223650461362f * 1.4426950408889634f;
                    float d0 = 0.f, d1 = 0.f;
#pragma unroll
                    for (int k = 0; k < 4; k++) {
                        l0[k] = l0[k] == NEG ? 0.f : ex2((l0[k] - m0) * sc); d0 += l0[k];
                        l1[k] = l1[k] == NEG ? 0.f : ex2((l1[k] - m1) * sc); d1 += l1[k];
                    }
                    d0 = __fdividef(1.0f, quad_sum(d0)); d1 = __fdividef(1.0f, quad_sum(d1));
                    const uint32_t pa0 = pack_bf16(l0[0] * d0, l0[1] * d0), pa2 = pack_bf16(l0[2] * d0, l0[3] * d0);
                    const uint32_t pa3 = pack_bf16(l1[0] * d1, l1[1] * d1), pb1 = pack_bf16(l1[2] * d1, l1[3] * d1);
                    float o[4][4];
#pragma unroll
                    for (int k = 0; k < 4; k++) o[k][0] = o[k][1] = o[k][2] = o[k][3] = 0.f;
                    const uint4 v0 = vv[2 * blk], v1 = vv[2 * blk + 1], v2 = vv[2 * blk + 2];
                    mma16816(o[0], pa0, 0u, pa2, pa3, movmat(v0.x), movmat(v1.x)); mma1688(o[0], 0u, pb1, movmat(v2.x));
                    mma16816(o[1], pa0, 0u, pa2, pa3, movmat(v0.y), movmat(v1.y)); mma1688(o[1], 0u, pb1, movmat(v2.y));
                    mma16816(o[2], pa0, 0u, pa2, pa3, movmat(v0.z), movmat(v1.z)); mma1688(o[2], 0u, pb1, movmat(v2.z));
                    mma16816(o[3], pa0, 0u, pa2, pa3, movmat(v0.w), movmat(v1.w)); mma1688(o[3], 0u, pb1, movmat(v2.w));
                    uint8_t* op = g_ou + ((size_t)(hb * 168 + c) * 64 + 2 * (16 * blk + g) + p) * 16;
                    const uint2 lo0 = make_uint2(pack_bf16(o[0][0], o[0][1]), pack_bf16(o[1][0], o[1][1]));
                    const uint2 hi0 = make_uint2(pack_bf16(o[2][0], o[2][1]), pack_bf16(o[3][0], o[3][1]));
                    const uint2 lo1 = make_uint2(pack_bf16(o[0][2], o[0][3]), pack_bf16(o[1][2], o[1][3]));
                    const uint2 hi1 = make_uint2(pack_bf16(o[2][2], o[2][3]), pack_bf16(o[3][2], o[3][3]));
                    if (!zlo) { *reinterpret_cast<uint2*>(op) = lo0; *reinterpret_cast<uint2*>(op + 256) = lo1; }
                    if (!zhi) { *reinterpret_cast<uint2*>(op + 8) = hi0; *reinterpret_cast<uint2*>(op + 264) = hi1; }
                }
            }
            fence_async_global();
            __syncwarp();
            if (lane == 0) { st_release(g_ouflag + hb * 16 + 8 + j, tgt); if (a == 0) TS(51); }
            bar_sync(7 + a, 160);
            if (lane == 0) {
                bulk_store(g_ou + ((size_t)hb * 168 + 56 + 14 * j) * 1024, sb + 2 * GSTRIDE + a * GRAN, GRAN);
                asm volatile("cp.async.bulk.wait_group.read 0;" ::: "memory");
                mbar_arrive(bars + 8 * B_USTFREE);
                mbar_arrive_remote(bars + 8 * B_USTFREE, h ^ 1);
                asm volatile("cp.async.bulk.wait_group 0;" ::: "memory");
                fence_async_global();
                st_release(g_ouflag + hb * 16 + j, tgt);
                if (a == 0) TS(52);
            }
        }
        __syncwarp();
        cluster_arrive_relaxed();
        cluster_wait();
    }
}

typedef CUresult (*PFN_encodeTiled)(CUtensorMap*, CUtensorMapDataType, cuuint32_t, void*, const cuuint64_t*, const cuuint64_t*,
                                    const cuuint32_t*, const cuuint32_t*, CUtensorMapInterleave, CUtensorMapSwizzle,
                                    CUtensorMapL2promotion, CUtensorMapFloatOOBfill);

void make_map(PFN_encodeTiled enc, CUtensorMap* tm, const void* ptr, int rank, const cuuint64_t* dims, const cuuint64_t* strides,
              const cuuint32_t* box) {
    cuuint32_t es[3] = {1, 1, 1};
    enc(tm, CU_TENSOR_MAP_DATA_TYPE_BFLOAT16, rank, const_cast<void*>(ptr), dims, strides, box, es, CU_TENSOR_MAP_INTERLEAVE_NONE,
        CU_TENSOR_MAP_SWIZZLE_128B, CU_TENSOR_MAP_L2_PROMOTION_L2_128B, CU_TENSOR_MAP_FLOAT_OOB_FILL_NONE);
}

}

extern "C" void kernel_launch(void* const* d_in, const int* in_sizes, int n_in, void* d_out, int out_size) {
    (void)in_sizes; (void)n_in; (void)out_size;
    PFN_encodeTiled enc = nullptr;
    cudaDriverEntryPointQueryResult st;
    cudaGetDriverEntryPoint("cuTensorMapEncodeTiled", (void**)&enc, cudaEnableDefault, &st);
    Params P;
    P.x = (const bf16*)d_in[0];
    P.wqkv = (const bf16*)d_in[1];
    P.wo = (const bf16*)d_in[2];
    P.win = (const bf16*)d_in[4];
    P.wsp = (const bf16*)d_in[5];
    P.bsp = (const bf16*)d_in[6];
    P.wout = (const bf16*)d_in[7];
    P.out = (bf16*)d_out;
    {
        cuuint64_t d[2] = {448, 2048}, s[1] = {896}; cuuint32_t b[2] = {64, 128};
        make_map(enc, &P.tm_x, P.x, 2, d, s, b);
    }
    {
        cuuint64_t d[3] = {112, 16, 448}, s[2] = {224, 3584}; cuuint32_t b[3] = {64, 1, 64};
        make_map(enc, &P.tm_win, P.win, 3, d, s, b);
    }
    {
        cuuint64_t d[3] = {168, 8, 448}, s[2] = {336, 2688}; cuuint32_t b[3] = {64, 1, 64};
        make_map(enc, &P.tm_wqkv, P.wqkv, 3, d, s, b);
    }
    {
        cuuint64_t d[2] = {2048, 2048}, s[1] = {4096}; cuuint32_t b[2] = {64, 64};
        make_map(enc, &P.tm_wsp, P.wsp, 2, d, s, b);
    }
    {
        cuuint64_t d[3] = {56, 8, 448}, s[2] = {112, 896}; cuuint32_t b[3] = {64, 1, 112};
        make_map(enc, &P.tm_wo, P.wo, 3, d, s, b);
    }
    {
        cuuint64_t d[3] = {56, 8, 896}, s[2] = {112, 896}; cuuint32_t b[3] = {64, 1, 112};
        make_map(enc, &P.tm_wout, P.wout, 3, d, s, b);
    }
    cudaFuncSetAttribute(fused_kernel, cudaFuncAttributeMaxDynamicSharedMemorySize, SMEM_BYTES);
    fused_kernel<<<128, 384, SMEM_BYTES>>>(P);
}
```

```cpp
#include <cuda_runtime.h>
#include <cuda_bf16.h>
#include <cuda.h>
#include <stdint.h>

#define NATT 2
#define P1_FENCE do {} while (0)
#define AUX_FENCE fence_async_global()
#define W0_POST 1
#define W0_PRE 1
#define USPLIT 6
#define PSTAG 150
#define UFLAG(hb, j) (g_ouflag + ((hb) * 16 + (j)) * 8)
#define POLL_SLEEP do {} while (0)
#define PF_SLEEP 120
#define Z2PIECES 2
#define LN_BAR 1 + wg, 128
#define GSPLIT 8
#define NORM_KB 0
#define Z1SCHED 0xECA86300u
#define ATT_START 9
#define L2PROMO CU_TENSOR_MAP_L2_PROMOTION_L2_128B
namespace {

typedef __nv_bfloat16 bf16;

__device__ __align__(1024) uint8_t g_z2t[16 * 8 * 28672];
__device__ __align__(1024) uint8_t g_ou[16 * 2 * 168 * 1024];
__device__ __align__(1024) uint4 g_wq[8 * 28 * 21 * 16];
__device__ __align__(128) unsigned g_wflag[8 * 32 * 8];
__device__ __align__(128) uint4 g_halo[16 * 8 * 14 * 32];
__device__ __align__(128) uint4 g_stats[16 * 8 * 64];
__device__ __align__(128) unsigned g_z2flag[8 * 32 * 8];
__device__ __align__(128) unsigned g_ouflag[32 * 16 * 8];
__device__ unsigned g_done;
#define TS3(c, k) do {} while (0)
#define TS2(c, k) do {} while (0)
#define TS(k) do {} while (0)
#define SPIN_CHECK(n, code) if (++n > (1u << 20)) __trap();
#define SPIN_CHECK2(n, code) if (++n > (1u << 24)) __trap();

constexpr uint32_t XN_OFF = 0;
constexpr uint32_t RINGA_OFF = 114688;
constexpr uint32_t Z2S_OFF = 200704;
constexpr uint32_t GBYTES = 30720;
constexpr uint64_t GSTAGE_KB = 0x703CC21E00ull;
constexpr uint32_t GRAN = 14336;
constexpr uint32_t WQ_BYTES = 21504;
constexpr uint32_t QQ_OFF = 92160, Q_PAR = 1088, Q_CH = 2176;
constexpr uint32_t KV_OFF = 145408, K_PAR = 1344, K_CH = 2688;
constexpr uint32_t OS_OFF = KV_OFF + 14 * K_CH;
static_assert(QQ_OFF + 8 * Q_CH <= 114688 && OS_OFF + 14336 <= 198656, "smem");
constexpr uint32_t BAR_OFF = 229376;
constexpr int B_FULL = 0, B_DONE = 16, B_FULLX = 32, B_Z2SFREE = 34, B_ATTFREE = 35, B_USTFREE = 36, B_OREADY = 37, B_STATS = 40, NBARS = 42;
constexpr int S_J2 = 7, S_J3 = 14, S_G2 = 21, S_C = 53;
constexpr uint32_t UFLAG_OFF = BAR_OFF + 384;
constexpr uint32_t STAT_OFF = BAR_OFF + 1024;
constexpr uint32_t SMEM_BYTES = BAR_OFF + 2048 + 1024;
__device__ __forceinline__ int tail_slot(int n) { return n >= 10 ? n - 10 : n >= 5 ? n - 5 : n; }
__device__ __forceinline__ uint32_t tail_a_kb(int n) { return (uint32_t)(0x1E70003CC4ull >> (8 * tail_slot(n))) & 255u; }
__device__ __forceinline__ uint32_t tail_w_kb(int n) { return (uint32_t)(0x5AB68CA89Aull >> (8 * tail_slot(n))) & 255u; }
__device__ __forceinline__ int tail_src(int n, int j) {
    return n == 2 ? j : n == 7 ? j ^ 1 : ((j & 6) + (int)((0x537604200000ull >> (4 * n)) & 15u)) & 7;
}
constexpr uint32_t SEL_OFF = BAR_OFF + 400;

__device__ __forceinline__ uint32_t smem_u32(const void* p) { return (uint32_t)__cvta_generic_to_shared(p); }
__device__ __forceinline__ void mbar_init(uint32_t bar, uint32_t count) {
    asm volatile("mbarrier.init.shared::cta.b64 [%0], %1;" ::"r"(bar), "r"(count) : "memory");
}
__device__ __forceinline__ void mbar_expect_tx(uint32_t bar, uint32_t bytes) {
    asm volatile("mbarrier.arrive.expect_tx.shared::cta.b64 _, [%0], %1;" ::"r"(bar), "r"(bytes) : "memory");
}
__device__ __forceinline__ void mbar_arrive(uint32_t bar) {
    asm volatile("mbarrier.arrive.shared::cta.b64 _, [%0];" ::"r"(bar) : "memory");
}
__device__ __forceinline__ void mbar_arrive_remote(uint32_t bar, uint32_t cta) {
    asm volatile("{\n.reg .b32 ra;\nmapa.shared::cluster.u32 ra, %0, %1;\nmbarrier.arrive.shared::cluster.b64 _, [ra];\n}\n" ::"r"(bar), "r"(cta) : "memory");
}
__device__ __forceinline__ void mbar_wait(uint32_t bar, uint32_t par) {
    asm volatile("{\n.reg .pred p;\n.reg .u32 n;\nmov.u32 n, 0;\n"
                 "W_LOOP:\nmbarrier.try_wait.parity.shared::cta.b64 p, [%0], %1;\n@p bra W_DONE;\n"
                 "add.u32 n, n, 1;\nsetp.lt.u32 p, n, 0x100000;\n@p bra W_LOOP;\ntrap;\nW_DONE:\n}\n" ::"r"(bar), "r"(par) : "memory");
}
__device__ __forceinline__ bool mbar_test(uint32_t bar, uint32_t par) {
    uint32_t ok;
    asm volatile("{\n.reg .pred p;\nmbarrier.test_wait.parity.shared::cta.b64 p, [%1], %2;\nselp.u32 %0, 1, 0, p;\n}\n" : "=r"(ok) : "r"(bar), "r"(par) : "memory");
    return ok != 0;
}
__host__ __device__ constexpr uint32_t wslot(int n) { return (uint32_t)(0x64321064321064ull >> (4 * n)) & 15u; }
__device__ __forceinline__ uint32_t gstage(int pos) { return ((uint32_t)(GSTAGE_KB >> (8 * pos)) & 255u) << 10; }
__device__ __forceinline__ uint32_t lds_u32(uint32_t a) {
    uint32_t v; asm volatile("ld.shared.u32 %0, [%1];" : "=r"(v) : "r"(a) : "memory"); return v;
}
__device__ __forceinline__ uint32_t lds_vol(uint32_t a) {
    uint32_t v; asm volatile("ld.volatile.shared.u32 %0, [%1];" : "=r"(v) : "r"(a) : "memory"); return v;
}
__device__ __forceinline__ void sts_vol(uint32_t a, uint32_t v) { asm volatile("st.volatile.shared.u32 [%0], %1;" ::"r"(a), "r"(v) : "memory"); }
__device__ __forceinline__ uint32_t full_bar(uint32_t bars, int step) { return bars + 8 * (B_FULL + (step & 15)); }
__device__ __forceinline__ uint32_t done_bar(uint32_t bars, int step) { return bars + 8 * (B_DONE + (step & 15)); }
__device__ __forceinline__ void wait_full(uint32_t bars, int step) { mbar_wait(full_bar(bars, step), (step >> 4) & 1); }
__device__ __forceinline__ void wait_done(uint32_t bars, int step) { mbar_wait(done_bar(bars, step), (step >> 4) & 1); }
__device__ __forceinline__ void tma_3d(uint32_t dst, const CUtensorMap* tm, int c0, int c1, int c2, uint32_t bar) {
    asm volatile("cp.async.bulk.tensor.3d.shared::cluster.global.mbarrier::complete_tx::bytes [%0], [%1, {%3, %4, %5}], [%2];"
                 ::"r"(dst), "l"(tm), "r"(bar), "r"(c0), "r"(c1), "r"(c2) : "memory");
}
__device__ __forceinline__ void tma_2d(uint32_t dst, const CUtensorMap* tm, int c0, int c1, uint32_t bar) {
    asm volatile("cp.async.bulk.tensor.2d.shared::cluster.global.mbarrier::complete_tx::bytes [%0], [%1, {%3, %4}], [%2];"
                 ::"r"(dst), "l"(tm), "r"(bar), "r"(c0), "r"(c1) : "memory");
}
__device__ __forceinline__ void tma_2d_mc(uint32_t dst, const CUtensorMap* tm, int c0, int c1, uint32_t bar) {
    asm volatile("cp.async.bulk.tensor.2d.shared::cluster.global.mbarrier::complete_tx::bytes.multicast::cluster [%0], [%1, {%3, %4}], [%2], %5;"
                 ::"r"(dst), "l"(tm), "r"(bar), "r"(c0), "r"(c1), "h"((uint16_t)3) : "memory");
}
__device__ __forceinline__ void bulk_load(uint32_t dst, const void* src, uint32_t bytes, uint32_t bar) {
    asm volatile("cp.async.bulk.shared::cluster.global.mbarrier::complete_tx::bytes [%0], [%1], %2, [%3];"
                 ::"r"(dst), "l"(src), "r"(bytes), "r"(bar) : "memory");
}
__device__ __forceinline__ void bulk_load_mc(uint32_t dst, const void* src, uint32_t bytes, uint32_t bar) {
    asm volatile("cp.async.bulk.shared::cluster.global.mbarrier::complete_tx::bytes.multicast::cluster [%0], [%1], %2, [%3], %4;"
                 ::"r"(dst), "l"(src), "r"(bytes), "r"(bar), "h"((uint16_t)3) : "memory");
}
__device__ __forceinline__ void bulk_store(void* dst, uint32_t src, uint32_t bytes) {
    asm volatile("cp.async.bulk.global.shared::cta.bulk_group [%0], [%1], %2;" ::"l"(dst), "r"(src), "r"(bytes) : "memory");
    asm volatile("cp.async.bulk.commit_group;" ::: "memory");
}
__device__ __forceinline__ void l2_prefetch(const void* p, uint32_t bytes) {
    asm volatile("cp.async.bulk.prefetch.L2.global [%0], %1;" ::"l"(p), "r"(bytes) : "memory");
}
__device__ __forceinline__ void wgmma_fence() { asm volatile("wgmma.fence.sync.aligned;" ::: "memory"); }
__device__ __forceinline__ void wgmma_commit() { asm volatile("wgmma.commit_group.sync.aligned;" ::: "memory"); }
template <int N> __device__ __forceinline__ void wgmma_wait() { asm volatile("wgmma.wait_group.sync.aligned %0;" ::"n"(N) : "memory"); }
template <int N> __device__ __forceinline__ void reg_fence(float (&d)[N]) {
#pragma unroll
    for (int k = 0; k < N; k++) asm volatile("" : "+f"(d[k])::"memory");
}
__device__ __forceinline__ uint32_t dlo(uint32_t addr, uint32_t lbo) { return ((addr & 0x3FFFF) >> 4) | ((lbo >> 4) << 16); }
constexpr uint32_t HI_SW128 = (1024 >> 4) | (1u << 30);
constexpr uint32_t HI_NOSW = (128 >> 4);
#define hi_sbo(sbo) ((sbo) / 16)
__device__ __forceinline__ void bar_sync(int id, int n) { asm volatile("bar.sync %0, %1;" ::"r"(id), "r"(n) : "memory"); }
__device__ __forceinline__ void bar_arrive(int id, int n) { asm volatile("bar.arrive %0, %1;" ::"r"(id), "r"(n) : "memory"); }
__device__ __forceinline__ void fence_async_smem() { asm volatile("fence.proxy.async.shared::cta;" ::: "memory"); }
__device__ __forceinline__ void fence_async_global() { asm volatile("fence.proxy.async.global;" ::: "memory"); }
__device__ __forceinline__ void cluster_arrive() { asm volatile("barrier.cluster.arrive.release.aligned;" ::: "memory"); }
__device__ __forceinline__ void cluster_arrive_relaxed() { asm volatile("barrier.cluster.arrive.relaxed.aligned;" ::: "memory"); }
__device__ __forceinline__ void mbar_arrive_cl(uint32_t cluster_addr) {
    asm volatile("mbarrier.arrive.shared::cluster.b64 _, [%0];" ::"r"(cluster_addr) : "memory");
}
__device__ __forceinline__ bool elect_one() {
    uint32_t p;
    asm volatile("{\n.reg .pred q;\nelect.sync _|q, 0xffffffff;\nselp.u32 %0, 1, 0, q;\n}\n" : "=r"(p));
    return p != 0;
}
__device__ __forceinline__ void cluster_wait() { asm volatile("barrier.cluster.wait.acquire.aligned;" ::: "memory"); }
__device__ __forceinline__ unsigned ld_acquire(const unsigned* p) {
    unsigned v; asm volatile("ld.acquire.gpu.global.u32 %0, [%1];" : "=r"(v) : "l"(p) : "memory"); return v;
}
__device__ __forceinline__ void st_release(unsigned* p, unsigned v) {
    asm volatile("st.release.gpu.global.u32 [%0], %1;" ::"l"(p), "r"(v) : "memory");
}
__device__ __forceinline__ void st_relaxed(unsigned* p, unsigned v) {
    asm volatile("st.relaxed.gpu.global.u32 [%0], %1;" ::"l"(p), "r"(v) : "memory");
}
__device__ __forceinline__ uint4 ld_relaxed_v4(const uint4* p) {
    uint4 v; asm volatile("ld.relaxed.gpu.global.v4.u32 {%0,%1,%2,%3}, [%4];" : "=r"(v.x), "=r"(v.y), "=r"(v.z), "=r"(v.w) : "l"(p) : "memory"); return v;
}
__device__ __forceinline__ void st_relaxed_v4(uint4* p, uint4 v) {
    asm volatile("st.relaxed.gpu.global.v4.u32 [%0], {%1,%2,%3,%4};" ::"l"(p), "r"(v.x), "r"(v.y), "r"(v.z), "r"(v.w) : "memory");
}
__device__ __forceinline__ uint4 ld_nc_v4(const void* p) {
    uint4 v; asm volatile("ld.global.nc.v4.u32 {%0,%1,%2,%3}, [%4];" : "=r"(v.x), "=r"(v.y), "=r"(v.z), "=r"(v.w) : "l"(p)); return v;
}
__device__ __forceinline__ uint4 ld_v4(const void* p) {
    uint4 v; asm volatile("ld.global.v4.u32 {%0,%1,%2,%3}, [%4];" : "=r"(v.x), "=r"(v.y), "=r"(v.z), "=r"(v.w) : "l"(p) : "memory"); return v;
}
__device__ __forceinline__ uint4 lds_v4(uint32_t a) {
    uint4 v; asm volatile("ld.shared.v4.u32 {%0,%1,%2,%3}, [%4];" : "=r"(v.x), "=r"(v.y), "=r"(v.z), "=r"(v.w) : "r"(a) : "memory"); return v;
}
__device__ __forceinline__ unsigned ld_relaxed(const unsigned* p) {
    unsigned v; asm volatile("ld.relaxed.gpu.global.u32 %0, [%1];" : "=r"(v) : "l"(p) : "memory"); return v;
}
__device__ __forceinline__ void sts_u32(uint32_t a, uint32_t v) { asm volatile("st.shared.u32 [%0], %1;" ::"r"(a), "r"(v) : "memory"); }
__device__ __forceinline__ void sts_v4(uint32_t a, uint4 v) {
    asm volatile("st.shared.v4.u32 [%0], {%1,%2,%3,%4};" ::"r"(a), "r"(v.x), "r"(v.y), "r"(v.z), "r"(v.w) : "memory");
}
__device__ __forceinline__ uint32_t pack_bf16(float lo, float hi) {
    uint32_t r; asm("cvt.rn.bf16x2.f32 %0, %1, %2;" : "=r"(r) : "f"(hi), "f"(lo)); return r;
}
__device__ __forceinline__ float bf_lo(uint32_t r) { return __uint_as_float(r << 16); }
__device__ __forceinline__ float bf_hi(uint32_t r) { return __uint_as_float(r & 0xffff0000u); }
__device__ __forceinline__ void unpack8(float (&f)[8], uint4 v) {
    f[0] = bf_lo(v.x); f[1] = bf_hi(v.x); f[2] = bf_lo(v.y); f[3] = bf_hi(v.y);
    f[4] = bf_lo(v.z); f[5] = bf_hi(v.z); f[6] = bf_lo(v.w); f[7] = bf_hi(v.w);
}
__device__ __forceinline__ uint32_t ld_nc_u32(const void* p) {
    uint32_t v; asm volatile("ld.global.nc.u32 %0, [%1];" : "=r"(v) : "l"(p)); return v;
}
__device__ __forceinline__ uint32_t ld_nc_u16(const void* p) {
    uint16_t v; asm volatile("ld.global.nc.u16 %0, [%1];" : "=h"(v) : "l"(p)); return v;
}
__device__ __forceinline__ uint32_t mul_bf16x2(uint32_t a, uint32_t b) {
    uint32_t r; asm("mul.rn.bf16x2 %0, %1, %2;" : "=r"(r) : "r"(a), "r"(b)); return r;
}
__device__ __forceinline__ uint32_t fma_bf16x2(uint32_t a, uint32_t b, uint32_t c) {
    uint32_t r; asm("fma.rn.bf16x2 %0, %1, %2, %3;" : "=r"(r) : "r"(a), "r"(b), "r"(c)); return r;
}
__device__ __forceinline__ uint32_t sub_bf16x2(uint32_t a, uint32_t b) {
    uint32_t r; asm("sub.rn.bf16x2 %0, %1, %2;" : "=r"(r) : "r"(a), "r"(b)); return r;
}
__device__ __forceinline__ void mma16816(float (&c)[4], uint32_t a0, uint32_t a1, uint32_t a2, uint32_t a3, uint32_t b0, uint32_t b1) {
    asm("mma.sync.aligned.m16n8k16.row.col.f32.bf16.bf16.f32 {%0,%1,%2,%3}, {%4,%5,%6,%7}, {%8,%9}, {%0,%1,%2,%3};"
        : "+f"(c[0]), "+f"(c[1]), "+f"(c[2]), "+f"(c[3]) : "r"(a0), "r"(a1), "r"(a2), "r"(a3), "r"(b0), "r"(b1));
}
__device__ __forceinline__ void mma1688(float (&c)[4], uint32_t a0, uint32_t a1, uint32_t b0) {
    asm volatile("mma.sync.aligned.m16n8k8.row.col.f32.bf16.bf16.f32 {%0,%1,%2,%3}, {%4,%5}, {%6}, {%0,%1,%2,%3};"
        : "+f"(c[0]), "+f"(c[1]), "+f"(c[2]), "+f"(c[3]) : "r"(a0), "r"(a1), "r"(b0));
}
__device__ __forceinline__ uint32_t movmat(uint32_t a) {
    uint32_t d; asm("movmatrix.sync.aligned.m8n8.trans.b16 %0, %1;" : "=r"(d) : "r"(a)); return d;
}
__device__ __forceinline__ void ldmat_x4(uint32_t& r0, uint32_t& r1, uint32_t& r2, uint32_t& r3, uint32_t a) {
    asm volatile("ldmatrix.sync.aligned.m8n8.x4.shared.b16 {%0,%1,%2,%3}, [%4];" : "=r"(r0), "=r"(r1), "=r"(r2), "=r"(r3) : "r"(a) : "memory");
}
__device__ __forceinline__ void stmat_x4(uint32_t a, uint32_t r0, uint32_t r1, uint32_t r2, uint32_t r3) {
    asm volatile("stmatrix.sync.aligned.m8n8.x4.shared.b16 [%0], {%1,%2,%3,%4};" ::"r"(a), "r"(r0), "r"(r1), "r"(r2), "r"(r3) : "memory");
}
__device__ __forceinline__ void stmat_x2(uint32_t a, uint32_t r0, uint32_t r1) {
    asm volatile("stmatrix.sync.aligned.m8n8.x2.shared.b16 [%0], {%1,%2};" ::"r"(a), "r"(r0), "r"(r1) : "memory");
}
__device__ __forceinline__ void stmat_x4_t(uint32_t a, uint32_t r0, uint32_t r1, uint32_t r2, uint32_t r3) {
    asm volatile("stmatrix.sync.aligned.m8n8.x4.trans.shared.b16 [%0], {%1,%2,%3,%4};" ::"r"(a), "r"(r0), "r"(r1), "r"(r2), "r"(r3) : "memory");
}
struct GeluC { float c0, c1, hr; };
__device__ __forceinline__ GeluC gelu_consts(float r) {
    GeluC c; c.c0 = 0.797884560803f * r; c.c1 = 0.035677408136f * r * r * r; c.hr = 0.5f * r; return c;
}
__device__ __forceinline__ float gelu_s(float a, const GeluC& c) {
    const float p = fmaf(a * a, c.c1, c.c0);
    float th; asm("tanh.approx.f32 %0, %1;" : "=f"(th) : "f"(a * p));
    const float h = a * c.hr;
    return fmaf(h, th, h);
}
__device__ __forceinline__ float ex2(float x) { float r; asm("ex2.approx.ftz.f32 %0, %1;" : "=f"(r) : "f"(x)); return r; }

#define PUBLISH(p, v) st_relaxed(p, v)

template <int TB, uint32_t AHI, uint32_t BHI>
__device__ __forceinline__ void wgmma_n64(float (&d)[32], uint32_t alo, uint32_t blo, bool acc) {
    if (acc) {
        asm volatile("{\n.reg .b64 da, db;\nmov.b64 da, {%32, %35};\nmov.b64 db, {%33, %36};\n"
            "wgmma.mma_async.sync.aligned.m64n64k16.f32.bf16.bf16 {%0, %1, %2, %3, %4, %5, %6, %7, %8, %9, %10, %11, %12, %13, %14, %15, %16, %17, %18, %19, %20, %21, %22, %23, %24, %25, %26, %27, %28, %29, %30, %31}, da, db, 1, 1, 1, 0, %34;\n}\n"
            : "+f"(d[0]), "+f"(d[1]), "+f"(d[2]), "+f"(d[3]), "+f"(d[4]), "+f"(d[5]), "+f"(d[6]), "+f"(d[7]), "+f"(d[8]), "+f"(d[9]), "+f"(d[10]), "+f"(d[11]), "+f"(d[12]), "+f"(d[13]), "+f"(d[14]), "+f"(d[15]), "+f"(d[16]), "+f"(d[17]), "+f"(d[18]), "+f"(d[19]), "+f"(d[20]), "+f"(d[21]), "+f"(d[22]), "+f"(d[23]), "+f"(d[24]), "+f"(d[25]), "+f"(d[26]), "+f"(d[27]), "+f"(d[28]), "+f"(d[29]), "+f"(d[30]), "+f"(d[31])
            : "r"(alo), "r"(blo), "n"(TB), "n"(AHI), "n"(BHI));
    } else {
        asm volatile("{\n.reg .b64 da, db;\nmov.b64 da, {%32, %35};\nmov.b64 db, {%33, %36};\n"
            "wgmma.mma_async.sync.aligned.m64n64k16.f32.bf16.bf16 {%0, %1, %2, %3, %4, %5, %6, %7, %8, %9, %10, %11, %12, %13, %14, %15, %16, %17, %18, %19, %20, %21, %22, %23, %24, %25, %26, %27, %28, %29, %30, %31}, da, db, 0, 1, 1, 0, %34;\n}\n"
            : "=f"(d[0]), "=f"(d[1]), "=f"(d[2]), "=f"(d[3]), "=f"(d[4]), "=f"(d[5]), "=f"(d[6]), "=f"(d[7]), "=f"(d[8]), "=f"(d[9]), "=f"(d[10]), "=f"(d[11]), "=f"(d[12]), "=f"(d[13]), "=f"(d[14]), "=f"(d[15]), "=f"(d[16]), "=f"(d[17]), "=f"(d[18]), "=f"(d[19]), "=f"(d[20]), "=f"(d[21]), "=f"(d[22]), "=f"(d[23]), "=f"(d[24]), "=f"(d[25]), "=f"(d[26]), "=f"(d[27]), "=f"(d[28]), "=f"(d[29]), "=f"(d[30]), "=f"(d[31])
            : "r"(alo), "r"(blo), "n"(TB), "n"(AHI), "n"(BHI));
    }
}
template <int TB, uint32_t AHI, uint32_t BHI>
__device__ __forceinline__ void wgmma_n72(float (&d)[36], uint32_t alo, uint32_t blo, bool acc) {
    if (acc) {
        asm volatile("{\n.reg .b64 da, db;\nmov.b64 da, {%36, %39};\nmov.b64 db, {%37, %40};\n"
            "wgmma.mma_async.sync.aligned.m64n72k16.f32.bf16.bf16 {%0, %1, %2, %3, %4, %5, %6, %7, %8, %9, %10, %11, %12, %13, %14, %15, %16, %17, %18, %19, %20, %21, %22, %23, %24, %25, %26, %27, %28, %29, %30, %31, %32, %33, %34, %35}, da, db, 1, 1, 1, 0, %38;\n}\n"
            : "+f"(d[0]), "+f"(d[1]), "+f"(d[2]), "+f"(d[3]), "+f"(d[4]), "+f"(d[5]), "+f"(d[6]), "+f"(d[7]), "+f"(d[8]), "+f"(d[9]), "+f"(d[10]), "+f"(d[11]), "+f"(d[12]), "+f"(d[13]), "+f"(d[14]), "+f"(d[15]), "+f"(d[16]), "+f"(d[17]), "+f"(d[18]), "+f"(d[19]), "+f"(d[20]), "+f"(d[21]), "+f"(d[22]), "+f"(d[23]), "+f"(d[24]), "+f"(d[25]), "+f"(d[26]), "+f"(d[27]), "+f"(d[28]), "+f"(d[29]), "+f"(d[30]), "+f"(d[31]), "+f"(d[32]), "+f"(d[33]), "+f"(d[34]), "+f"(d[35])
            : "r"(alo), "r"(blo), "n"(TB), "n"(AHI), "n"(BHI));
    } else {
        asm volatile("{\n.reg .b64 da, db;\nmov.b64 da, {%36, %39};\nmov.b64 db, {%37, %40};\n"
            "wgmma.mma_async.sync.aligned.m64n72k16.f32.bf16.bf16 {%0, %1, %2, %3, %4, %5, %6, %7, %8, %9, %10, %11, %12, %13, %14, %15, %16, %17, %18, %19, %20, %21, %22, %23, %24, %25, %26, %27, %28, %29, %30, %31, %32, %33, %34, %35}, da, db, 0, 1, 1, 0, %38;\n}\n"
            : "=f"(d[0]), "=f"(d[1]), "=f"(d[2]), "=f"(d[3]), "=f"(d[4]), "=f"(d[5]), "=f"(d[6]), "=f"(d[7]), "=f"(d[8]), "=f"(d[9]), "=f"(d[10]), "=f"(d[11]), "=f"(d[12]), "=f"(d[13]), "=f"(d[14]), "=f"(d[15]), "=f"(d[16]), "=f"(d[17]), "=f"(d[18]), "=f"(d[19]), "=f"(d[20]), "=f"(d[21]), "=f"(d[22]), "=f"(d[23]), "=f"(d[24]), "=f"(d[25]), "=f"(d[26]), "=f"(d[27]), "=f"(d[28]), "=f"(d[29]), "=f"(d[30]), "=f"(d[31]), "=f"(d[32]), "=f"(d[33]), "=f"(d[34]), "=f"(d[35])
            : "r"(alo), "r"(blo), "n"(TB), "n"(AHI), "n"(BHI));
    }
}
template <int TB, uint32_t AHI, uint32_t BHI>
__device__ __forceinline__ void wgmma_n112(float (&d)[56], uint32_t alo, uint32_t blo, bool acc) {
    if (acc) {
        asm volatile("{\n.reg .b64 da, db;\nmov.b64 da, {%56, %59};\nmov.b64 db, {%57, %60};\n"
            "wgmma.mma_async.sync.aligned.m64n112k16.f32.bf16.bf16 {%0, %1, %2, %3, %4, %5, %6, %7, %8, %9, %10, %11, %12, %13, %14, %15, %16, %17, %18, %19, %20, %21, %22, %23, %24, %25, %26, %27, %28, %29, %30, %31, %32, %33, %34, %35, %36, %37, %38, %39, %40, %41, %42, %43, %44, %45, %46, %47, %48, %49, %50, %51, %52, %53, %54, %55}, da, db, 1, 1, 1, 0, %58;\n}\n"
            : "+f"(d[0]), "+f"(d[1]), "+f"(d[2]), "+f"(d[3]), "+f"(d[4]), "+f"(d[5]), "+f"(d[6]), "+f"(d[7]), "+f"(d[8]), "+f"(d[9]), "+f"(d[10]), "+f"(d[11]), "+f"(d[12]), "+f"(d[13]), "+f"(d[14]), "+f"(d[15]), "+f"(d[16]), "+f"(d[17]), "+f"(d[18]), "+f"(d[19]), "+f"(d[20]), "+f"(d[21]), "+f"(d[22]), "+f"(d[23]), "+f"(d[24]), "+f"(d[25]), "+f"(d[26]), "+f"(d[27]), "+f"(d[28]), "+f"(d[29]), "+f"(d[30]), "+f"(d[31]), "+f"(d[32]), "+f"(d[33]), "+f"(d[34]), "+f"(d[35]), "+f"(d[36]), "+f"(d[37]), "+f"(d[38]), "+f"(d[39]), "+f"(d[40]), "+f"(d[41]), "+f"(d[42]), "+f"(d[43]), "+f"(d[44]), "+f"(d[45]), "+f"(d[46]), "+f"(d[47]), "+f"(d[48]), "+f"(d[49]), "+f"(d[50]), "+f"(d[51]), "+f"(d[52]), "+f"(d[53]), "+f"(d[54]), "+f"(d[55])
            : "r"(alo), "r"(blo), "n"(TB), "n"(AHI), "n"(BHI));
    } else {
        asm volatile("{\n.reg .b64 da, db;\nmov.b64 da, {%56, %59};\nmov.b64 db, {%57, %60};\n"
            "wgmma.mma_async.sync.aligned.m64n112k16.f32.bf16.bf16 {%0, %1, %2, %3, %4, %5, %6, %7, %8, %9, %10, %11, %12, %13, %14, %15, %16, %17, %18, %19, %20, %21, %22, %23, %24, %25, %26, %27, %28, %29, %30, %31, %32, %33, %34, %35, %36, %37, %38, %39, %40, %41, %42, %43, %44, %45, %46, %47, %48, %49, %50, %51, %52, %53, %54, %55}, da, db, 0, 1, 1, 0, %58;\n}\n"
            : "=f"(d[0]), "=f"(d[1]), "=f"(d[2]), "=f"(d[3]), "=f"(d[4]), "=f"(d[5]), "=f"(d[6]), "=f"(d[7]), "=f"(d[8]), "=f"(d[9]), "=f"(d[10]), "=f"(d[11]), "=f"(d[12]), "=f"(d[13]), "=f"(d[14]), "=f"(d[15]), "=f"(d[16]), "=f"(d[17]), "=f"(d[18]), "=f"(d[19]), "=f"(d[20]), "=f"(d[21]), "=f"(d[22]), "=f"(d[23]), "=f"(d[24]), "=f"(d[25]), "=f"(d[26]), "=f"(d[27]), "=f"(d[28]), "=f"(d[29]), "=f"(d[30]), "=f"(d[31]), "=f"(d[32]), "=f"(d[33]), "=f"(d[34]), "=f"(d[35]), "=f"(d[36]), "=f"(d[37]), "=f"(d[38]), "=f"(d[39]), "=f"(d[40]), "=f"(d[41]), "=f"(d[42]), "=f"(d[43]), "=f"(d[44]), "=f"(d[45]), "=f"(d[46]), "=f"(d[47]), "=f"(d[48]), "=f"(d[49]), "=f"(d[50]), "=f"(d[51]), "=f"(d[52]), "=f"(d[53]), "=f"(d[54]), "=f"(d[55])
            : "r"(alo), "r"(blo), "n"(TB), "n"(AHI), "n"(BHI));
    }
}
template <int TB, uint32_t AHI, uint32_t BHI>
__device__ __forceinline__ void wgmma_n112_p(float (&d)[56], uint32_t alo, uint32_t blo, int acc) {
    asm volatile("{\n.reg .b64 da, db;\n.reg .pred p;\nsetp.ne.b32 p, %61, 0;\nmov.b64 da, {%56, %59};\nmov.b64 db, {%57, %60};\n"
        "wgmma.mma_async.sync.aligned.m64n112k16.f32.bf16.bf16 {%0, %1, %2, %3, %4, %5, %6, %7, %8, %9, %10, %11, %12, %13, %14, %15, %16, %17, %18, %19, %20, %21, %22, %23, %24, %25, %26, %27, %28, %29, %30, %31, %32, %33, %34, %35, %36, %37, %38, %39, %40, %41, %42, %43, %44, %45, %46, %47, %48, %49, %50, %51, %52, %53, %54, %55}, da, db, p, 1, 1, 0, %58;\n}\n"
        : "+f"(d[0]), "+f"(d[1]), "+f"(d[2]), "+f"(d[3]), "+f"(d[4]), "+f"(d[5]), "+f"(d[6]), "+f"(d[7]), "+f"(d[8]), "+f"(d[9]), "+f"(d[10]), "+f"(d[11]), "+f"(d[12]), "+f"(d[13]), "+f"(d[14]), "+f"(d[15]), "+f"(d[16]), "+f"(d[17]), "+f"(d[18]), "+f"(d[19]), "+f"(d[20]), "+f"(d[21]), "+f"(d[22]), "+f"(d[23]), "+f"(d[24]), "+f"(d[25]), "+f"(d[26]), "+f"(d[27]), "+f"(d[28]), "+f"(d[29]), "+f"(d[30]), "+f"(d[31]), "+f"(d[32]), "+f"(d[33]), "+f"(d[34]), "+f"(d[35]), "+f"(d[36]), "+f"(d[37]), "+f"(d[38]), "+f"(d[39]), "+f"(d[40]), "+f"(d[41]), "+f"(d[42]), "+f"(d[43]), "+f"(d[44]), "+f"(d[45]), "+f"(d[46]), "+f"(d[47]), "+f"(d[48]), "+f"(d[49]), "+f"(d[50]), "+f"(d[51]), "+f"(d[52]), "+f"(d[53]), "+f"(d[54]), "+f"(d[55])
        : "r"(alo), "r"(blo), "n"(TB), "n"(AHI), "n"(BHI), "r"(acc));
}
template <int TB, uint32_t AHI, uint32_t BHI>
__device__ __forceinline__ void wgmma_n168(float (&d)[84], uint32_t alo, uint32_t blo, bool acc) {
    if (acc) {
        asm volatile("{\n.reg .b64 da, db;\nmov.b64 da, {%84, %87};\nmov.b64 db, {%85, %88};\n"
            "wgmma.mma_async.sync.aligned.m64n168k16.f32.bf16.bf16 {%0, %1, %2, %3, %4, %5, %6, %7, %8, %9, %10, %11, %12, %13, %14, %15, %16, %17, %18, %19, %20, %21, %22, %23, %24, %25, %26, %27, %28, %29, %30, %31, %32, %33, %34, %35, %36, %37, %38, %39, %40, %41, %42, %43, %44, %45, %46, %47, %48, %49, %50, %51, %52, %53, %54, %55, %56, %57, %58, %59, %60, %61, %62, %63, %64, %65, %66, %67, %68, %69, %70, %71, %72, %73, %74, %75, %76, %77, %78, %79, %80, %81, %82, %83}, da, db, 1, 1, 1, 0, %86;\n}\n"
            : "+f"(d[0]), "+f"(d[1]), "+f"(d[2]), "+f"(d[3]), "+f"(d[4]), "+f"(d[5]), "+f"(d[6]), "+f"(d[7]), "+f"(d[8]), "+f"(d[9]), "+f"(d[10]), "+f"(d[11]), "+f"(d[12]), "+f"(d[13]), "+f"(d[14]), "+f"(d[15]), "+f"(d[16]), "+f"(d[17]), "+f"(d[18]), "+f"(d[19]), "+f"(d[20]), "+f"(d[21]), "+f"(d[22]), "+f"(d[23]), "+f"(d[24]), "+f"(d[25]), "+f"(d[26]), "+f"(d[27]), "+f"(d[28]), "+f"(d[29]), "+f"(d[30]), "+f"(d[31]), "+f"(d[32]), "+f"(d[33]), "+f"(d[34]), "+f"(d[35]), "+f"(d[36]), "+f"(d[37]), "+f"(d[38]), "+f"(d[39]), "+f"(d[40]), "+f"(d[41]), "+f"(d[42]), "+f"(d[43]), "+f"(d[44]), "+f"(d[45]), "+f"(d[46]), "+f"(d[47]), "+f"(d[48]), "+f"(d[49]), "+f"(d[50]), "+f"(d[51]), "+f"(d[52]), "+f"(d[53]), "+f"(d[54]), "+f"(d[55]), "+f"(d[56]), "+f"(d[57]), "+f"(d[58]), "+f"(d[59]), "+f"(d[60]), "+f"(d[61]), "+f"(d[62]), "+f"(d[63]), "+f"(d[64]), "+f"(d[65]), "+f"(d[66]), "+f"(d[67]), "+f"(d[68]), "+f"(d[69]), "+f"(d[70]), "+f"(d[71]), "+f"(d[72]), "+f"(d[73]), "+f"(d[74]), "+f"(d[75]), "+f"(d[76]), "+f"(d[77]), "+f"(d[78]), "+f"(d[79]), "+f"(d[80]), "+f"(d[81]), "+f"(d[82]), "+f"(d[83])
            : "r"(alo), "r"(blo), "n"(TB), "n"(AHI), "n"(BHI));
    } else {
        asm volatile("{\n.reg .b64 da, db;\nmov.b64 da, {%84, %87};\nmov.b64 db, {%85, %88};\n"
            "wgmma.mma_async.sync.aligned.m64n168k16.f32.bf16.bf16 {%0, %1, %2, %3, %4, %5, %6, %7, %8, %9, %10, %11, %12, %13, %14, %15, %16, %17, %18, %19, %20, %21, %22, %23, %24, %25, %26, %27, %28, %29, %30, %31, %32, %33, %34, %35, %36, %37, %38, %39, %40, %41, %42, %43, %44, %45, %46, %47, %48, %49, %50, %51, %52, %53, %54, %55, %56, %57, %58, %59, %60, %61, %62, %63, %64, %65, %66, %67, %68, %69, %70, %71, %72, %73, %74, %75, %76, %77, %78, %79, %80, %81, %82, %83}, da, db, 0, 1, 1, 0, %86;\n}\n"
            : "=f"(d[0]), "=f"(d[1]), "=f"(d[2]), "=f"(d[3]), "=f"(d[4]), "=f"(d[5]), "=f"(d[6]), "=f"(d[7]), "=f"(d[8]), "=f"(d[9]), "=f"(d[10]), "=f"(d[11]), "=f"(d[12]), "=f"(d[13]), "=f"(d[14]), "=f"(d[15]), "=f"(d[16]), "=f"(d[17]), "=f"(d[18]), "=f"(d[19]), "=f"(d[20]), "=f"(d[21]), "=f"(d[22]), "=f"(d[23]), "=f"(d[24]), "=f"(d[25]), "=f"(d[26]), "=f"(d[27]), "=f"(d[28]), "=f"(d[29]), "=f"(d[30]), "=f"(d[31]), "=f"(d[32]), "=f"(d[33]), "=f"(d[34]), "=f"(d[35]), "=f"(d[36]), "=f"(d[37]), "=f"(d[38]), "=f"(d[39]), "=f"(d[40]), "=f"(d[41]), "=f"(d[42]), "=f"(d[43]), "=f"(d[44]), "=f"(d[45]), "=f"(d[46]), "=f"(d[47]), "=f"(d[48]), "=f"(d[49]), "=f"(d[50]), "=f"(d[51]), "=f"(d[52]), "=f"(d[53]), "=f"(d[54]), "=f"(d[55]), "=f"(d[56]), "=f"(d[57]), "=f"(d[58]), "=f"(d[59]), "=f"(d[60]), "=f"(d[61]), "=f"(d[62]), "=f"(d[63]), "=f"(d[64]), "=f"(d[65]), "=f"(d[66]), "=f"(d[67]), "=f"(d[68]), "=f"(d[69]), "=f"(d[70]), "=f"(d[71]), "=f"(d[72]), "=f"(d[73]), "=f"(d[74]), "=f"(d[75]), "=f"(d[76]), "=f"(d[77]), "=f"(d[78]), "=f"(d[79]), "=f"(d[80]), "=f"(d[81]), "=f"(d[82]), "=f"(d[83])
            : "r"(alo), "r"(blo), "n"(TB), "n"(AHI), "n"(BHI));
    }
}
template <int TB, uint32_t BHI>
__device__ __forceinline__ void wgmma_rs_n32(float (&d)[16], uint32_t a0, uint32_t a1, uint32_t a2, uint32_t a3, uint32_t blo, bool acc) {
    if (acc) {
        asm volatile("{\n.reg .b64 db;\nmov.b64 db, {%20, %22};\n"
            "wgmma.mma_async.sync.aligned.m64n32k16.f32.bf16.bf16 {%0, %1, %2, %3, %4, %5, %6, %7, %8, %9, %10, %11, %12, %13, %14, %15}, {%16, %17, %18, %19}, db, 1, 1, 1, %21;\n}\n"
            : "+f"(d[0]), "+f"(d[1]), "+f"(d[2]), "+f"(d[3]), "+f"(d[4]), "+f"(d[5]), "+f"(d[6]), "+f"(d[7]), "+f"(d[8]), "+f"(d[9]), "+f"(d[10]), "+f"(d[11]), "+f"(d[12]), "+f"(d[13]), "+f"(d[14]), "+f"(d[15])
            : "r"(a0), "r"(a1), "r"(a2), "r"(a3), "r"(blo), "n"(TB), "n"(BHI));
    } else {
        asm volatile("{\n.reg .b64 db;\nmov.b64 db, {%20, %22};\n"
            "wgmma.mma_async.sync.aligned.m64n32k16.f32.bf16.bf16 {%0, %1, %2, %3, %4, %5, %6, %7, %8, %9, %10, %11, %12, %13, %14, %15}, {%16, %17, %18, %19}, db, 0, 1, 1, %21;\n}\n"
            : "=f"(d[0]), "=f"(d[1]), "=f"(d[2]), "=f"(d[3]), "=f"(d[4]), "=f"(d[5]), "=f"(d[6]), "=f"(d[7]), "=f"(d[8]), "=f"(d[9]), "=f"(d[10]), "=f"(d[11]), "=f"(d[12]), "=f"(d[13]), "=f"(d[14]), "=f"(d[15])
            : "r"(a0), "r"(a1), "r"(a2), "r"(a3), "r"(blo), "n"(TB), "n"(BHI));
    }
}
template <int TB, uint32_t BHI>
__device__ __forceinline__ void wgmma_rs_n112(float (&d)[56], uint32_t a0, uint32_t a1, uint32_t a2, uint32_t a3, uint32_t blo, bool acc) {
    if (acc) {
        asm volatile("{\n.reg .b64 db;\nmov.b64 db, {%60, %62};\n"
            "wgmma.mma_async.sync.aligned.m64n112k16.f32.bf16.bf16 {%0, %1, %2, %3, %4, %5, %6, %7, %8, %9, %10, %11, %12, %13, %14, %15, %16, %17, %18, %19, %20, %21, %22, %23, %24, %25, %26, %27, %28, %29, %30, %31, %32, %33, %34, %35, %36, %37, %38, %39, %40, %41, %42, %43, %44, %45, %46, %47, %48, %49, %50, %51, %52, %53, %54, %55}, {%56, %57, %58, %59}, db, 1, 1, 1, %61;\n}\n"
            : "+f"(d[0]), "+f"(d[1]), "+f"(d[2]), "+f"(d[3]), "+f"(d[4]), "+f"(d[5]), "+f"(d[6]), "+f"(d[7]), "+f"(d[8]), "+f"(d[9]), "+f"(d[10]), "+f"(d[11]), "+f"(d[12]), "+f"(d[13]), "+f"(d[14]), "+f"(d[15]), "+f"(d[16]), "+f"(d[17]), "+f"(d[18]), "+f"(d[19]), "+f"(d[20]), "+f"(d[21]), "+f"(d[22]), "+f"(d[23]), "+f"(d[24]), "+f"(d[25]), "+f"(d[26]), "+f"(d[27]), "+f"(d[28]), "+f"(d[29]), "+f"(d[30]), "+f"(d[31]), "+f"(d[32]), "+f"(d[33]), "+f"(d[34]), "+f"(d[35]), "+f"(d[36]), "+f"(d[37]), "+f"(d[38]), "+f"(d[39]), "+f"(d[40]), "+f"(d[41]), "+f"(d[42]), "+f"(d[43]), "+f"(d[44]), "+f"(d[45]), "+f"(d[46]), "+f"(d[47]), "+f"(d[48]), "+f"(d[49]), "+f"(d[50]), "+f"(d[51]), "+f"(d[52]), "+f"(d[53]), "+f"(d[54]), "+f"(d[55])
            : "r"(a0), "r"(a1), "r"(a2), "r"(a3), "r"(blo), "n"(TB), "n"(BHI));
    } else {
        asm volatile("{\n.reg .b64 db;\nmov.b64 db, {%60, %62};\n"
            "wgmma.mma_async.sync.aligned.m64n112k16.f32.bf16.bf16 {%0, %1, %2, %3, %4, %5, %6, %7, %8, %9, %10, %11, %12, %13, %14, %15, %16, %17, %18, %19, %20, %21, %22, %23, %24, %25, %26, %27, %28, %29, %30, %31, %32, %33, %34, %35, %36, %37, %38, %39, %40, %41, %42, %43, %44, %45, %46, %47, %48, %49, %50, %51, %52, %53, %54, %55}, {%56, %57, %58, %59}, db, 0, 1, 1, %61;\n}\n"
            : "=f"(d[0]), "=f"(d[1]), "=f"(d[2]), "=f"(d[3]), "=f"(d[4]), "=f"(d[5]), "=f"(d[6]), "=f"(d[7]), "=f"(d[8]), "=f"(d[9]), "=f"(d[10]), "=f"(d[11]), "=f"(d[12]), "=f"(d[13]), "=f"(d[14]), "=f"(d[15]), "=f"(d[16]), "=f"(d[17]), "=f"(d[18]), "=f"(d[19]), "=f"(d[20]), "=f"(d[21]), "=f"(d[22]), "=f"(d[23]), "=f"(d[24]), "=f"(d[25]), "=f"(d[26]), "=f"(d[27]), "=f"(d[28]), "=f"(d[29]), "=f"(d[30]), "=f"(d[31]), "=f"(d[32]), "=f"(d[33]), "=f"(d[34]), "=f"(d[35]), "=f"(d[36]), "=f"(d[37]), "=f"(d[38]), "=f"(d[39]), "=f"(d[40]), "=f"(d[41]), "=f"(d[42]), "=f"(d[43]), "=f"(d[44]), "=f"(d[45]), "=f"(d[46]), "=f"(d[47]), "=f"(d[48]), "=f"(d[49]), "=f"(d[50]), "=f"(d[51]), "=f"(d[52]), "=f"(d[53]), "=f"(d[54]), "=f"(d[55])
            : "r"(a0), "r"(a1), "r"(a2), "r"(a3), "r"(blo), "n"(TB), "n"(BHI));
    }
}

struct Params {
    CUtensorMap tm_x;
    CUtensorMap tm_win;
    CUtensorMap tm_wsp;
    CUtensorMap tm_wqkv;
    CUtensorMap tm_wo;
    CUtensorMap tm_wout;
    const bf16* x;
    const bf16* wqkv;
    const bf16* wo;
    const bf16* win;
    const bf16* wsp;
    const bf16* bsp;
    const bf16* wout;
    bf16* out;
};

__device__ __forceinline__ float quad_sum(float v) {
    v += __shfl_xor_sync(0xffffffffu, v, 1);
    v += __shfl_xor_sync(0xffffffffu, v, 2);
    return v;
}

__device__ __forceinline__ void quad_transpose(uint32_t& v0, uint32_t& v1, uint32_t& v2, uint32_t& v3, int t) {
    const bool o1 = t & 1, o2 = t & 2;
    uint32_t x0 = __shfl_xor_sync(0xffffffffu, o1 ? v0 : v1, 1), x1 = __shfl_xor_sync(0xffffffffu, o1 ? v2 : v3, 1);
    if (o1) { v0 = x0; v2 = x1; } else { v1 = x0; v3 = x1; }
    x0 = __shfl_xor_sync(0xffffffffu, o2 ? v0 : v2, 2); x1 = __shfl_xor_sync(0xffffffffu, o2 ? v1 : v3, 2);
    if (o2) { v0 = x0; v1 = x1; } else { v2 = x0; v3 = x1; }
}

__global__ void __cluster_dims__(2, 1, 1) __launch_bounds__(384, 1)
fused_kernel(const __grid_constant__ Params P) {
    extern __shared__ __align__(1024) uint8_t smem_raw[];
    const uint32_t sb = (smem_u32(smem_raw) + 1023u) & ~1023u;
    const uint32_t bars = sb + BAR_OFF;
    const int h = blockIdx.x & 1;
    const int pr = blockIdx.x >> 1;
    const int i = pr & 15, jj = pr >> 4, j = 2 * jj + h;
    const int lane = threadIdx.x & 31, g = lane >> 2, t = lane & 3;
    const int warp = __shfl_sync(0xffffffffu, threadIdx.x >> 5, 0);
    if (lane == 0) {
        if (warp == 8) {
            mbar_init(bars + 8 * B_FULLX, 1);
            mbar_init(bars + 8 * (B_FULLX + 1), 1);
            mbar_expect_tx(bars + 8 * B_FULLX, 4 * GRAN);
            mbar_expect_tx(bars + 8 * (B_FULLX + 1), 4 * GRAN);
#pragma unroll 1
            for (int r = 0; r < 14; r++) {
                const int hf = r >= 7, kb = r - 7 * hf;
                tma_2d(sb + XN_OFF + kb * 16384 + hf * 8192, &P.tm_x, kb * 64, i * 128 + hf * 64, bars + 8 * (B_FULLX + hf));
            }
        } else if (warp < 8) {
            mbar_init(bars + 8 * (B_FULL + warp), 1);
            mbar_init(bars + 8 * (B_FULL + 8 + warp), 1);
            mbar_init(bars + 8 * (B_DONE + warp), 4);
            mbar_init(bars + 8 * (B_DONE + 8 + warp), 4);
        } else {
            mbar_init(bars + 8 * (B_Z2SFREE + warp - 9), 2);
            if (warp == 9) {
                sts_u32(sb + UFLAG_OFF, 0u);
                sts_v4(sb + SEL_OFF, make_uint4(0u, 1u, 2u, 3u));
                sts_v4(sb + SEL_OFF + 16, make_uint4(4u, 0u, 0u, 0u));
                sts_v4(sb + SEL_OFF + 32, make_uint4(0u, 0u, 0u, 0u));
                sts_u32(sb + SEL_OFF + 48, 12u);
                asm volatile("prefetch.tensormap [%0];" ::"l"(&P.tm_win) : "memory");
                asm volatile("prefetch.tensormap [%0];" ::"l"(&P.tm_wqkv) : "memory");
            }
            mbar_init(bars + 8 * (B_OREADY + warp - 9), 1);
            if (warp > 9) mbar_init(bars + 8 * (B_STATS + warp - 10), 1);
        }
        asm volatile("fence.mbarrier_init.release.cluster;" ::: "memory");
    }
    __syncwarp();
    cluster_arrive_relaxed();

    if (warp < 8) {
        const int wg = warp >> 2, w = warp & 3;
        const bool sig2 = (lane == 0) && (w < 2);
        uint32_t rdone;
        asm volatile("mapa.shared::cluster.u32 %0, %1, %2;" : "=r"(rdone) : "r"(bars + 8 * B_DONE), "r"(h ^ (w & 1)));
#define SIGNAL_LOCAL(step) do { if (sig2) mbar_arrive(bars + 8 * (B_DONE + ((step) & 15))); } while (0)
#define SIGNAL_DONE(step) do { if (sig2) mbar_arrive_cl(rdone + 8 * ((step) & 15)); } while (0)
        const int row0 = i * 128 + warp * 16 + g;
        uint32_t xr[16];
        asm volatile("setmaxnreg.inc.sync.aligned.u32 216;");
        bar_sync(9, 384);
        if (threadIdx.x == 0) TS(53);
        const uint32_t dA_xn = dlo(sb + XN_OFF + wg * 8192, 16);
        const uint32_t dB_ra = dlo(sb + RINGA_OFF, 8192);
        float acc_a[56], acc_b[56], acc_c[84];
        float rs0, rs1;
        unsigned epoch;
        {
            uint32_t xf[28][4];
            const uint32_t la = sb + XN_OFF + (warp * 16 + (lane & 15)) * 128 + (((lane >> 4) ^ (lane & 7)) << 4);
            mbar_wait(bars + 8 * (B_FULLX + wg), 0);
            if (threadIdx.x == 0) TS(56);
            if (threadIdx.x == 128) TS(15);
#pragma unroll
            for (int c = 0; c < 28; c++) ldmat_x4(xf[c][0], xf[c][1], xf[c][2], xf[c][3], (la ^ ((c & 3) << 5)) + (c >> 2) * 16384);
#pragma unroll
            for (int q = 0; q < 4; q++) ldmat_x4(xr[4 * q], xr[4 * q + 1], xr[4 * q + 2], xr[4 * q + 3], (la ^ (q << 5)) + min(j, 6) * 16384);
            float sA[4] = {0.f, 0.f, 0.f, 0.f}, sB[4] = {0.f, 0.f, 0.f, 0.f}, sC[4] = {0.f, 0.f, 0.f, 0.f}, sD[4] = {0.f, 0.f, 0.f, 0.f};
            const uint32_t ONES = 0x3F803F80u;
#pragma unroll
            for (int c = 0; c < 28; c += 4) {
                mma16816(sA, xf[c][0], xf[c][1], xf[c][2], xf[c][3], ONES, ONES);
                mma16816(sB, xf[c + 1][0], xf[c + 1][1], xf[c + 1][2], xf[c + 1][3], ONES, ONES);
                mma16816(sC, xf[c + 2][0], xf[c + 2][1], xf[c + 2][2], xf[c + 2][3], ONES, ONES);
                mma16816(sD, xf[c + 3][0], xf[c + 3][1], xf[c + 3][2], xf[c + 3][3], ONES, ONES);
            }
            const float ma = ((sA[0] + sB[0]) + (sC[0] + sD[0])) * (1.0f / 448.0f), mb = ((sA[2] + sB[2]) + (sC[2] + sD[2])) * (1.0f / 448.0f);
            const uint32_t ma2 = pack_bf16(ma, ma), mb2 = pack_bf16(mb, mb);
            const float dma = ma - bf_lo(ma2), dmb = mb - bf_lo(mb2);
            if (threadIdx.x == 0) TS(57);
            if (threadIdx.x == 128) TS(12);
#define CENTRE(kb_) do { \
                _Pragma("unroll") \
                for (int c = 4 * (kb_); c < 4 * (kb_) + 4; c++) { \
                    xf[c][0] = sub_bf16x2(xf[c][0], ma2); xf[c][1] = sub_bf16x2(xf[c][1], mb2); \
                    xf[c][2] = sub_bf16x2(xf[c][2], ma2); xf[c][3] = sub_bf16x2(xf[c][3], mb2); \
                    asm volatile("" : "+r"(xf[c][0]), "+r"(xf[c][1]), "+r"(xf[c][2]), "+r"(xf[c][3])); \
                } \
            } while (0)
#define XSTORE(kb_) do { \
                _Pragma("unroll") \
                for (int c = 4 * (kb_); c < 4 * (kb_) + 4; c++) stmat_x4((la ^ ((c & 3) << 5)) + (c >> 2) * 16384, xf[c][0], xf[c][1], xf[c][2], xf[c][3]); \
            } while (0)
            CENTRE(0);
            float qa = 0.f, qb = 0.f, qa2 = 0.f, qb2 = 0.f;
            constexpr uint64_t VSCHED = 0x1C16100C08040000ull;
#pragma unroll
            for (int kb = 0; kb < 7; kb++) {
                wait_full(bars, kb);
                TS2(threadIdx.x == 0, kb);
                wgmma_fence();
#pragma unroll
                for (int k = 0; k < 4; k++)
                    wgmma_rs_n112<1, HI_SW128>(acc_a, xf[4 * kb + k][0], xf[4 * kb + k][1], xf[4 * kb + k][2], xf[4 * kb + k][3],
                                               dB_ra + wslot(kb) * 1024 + k * 128, (kb | k) != 0);
                wgmma_commit();
                if (kb < 6) CENTRE(kb + 1);
                if (kb > 0) { wgmma_wait<1>(); SIGNAL_LOCAL(kb - 1); }
                if (kb == 1) {
                    epoch = ld_relaxed(&g_done);
                    if (t == 0) st_relaxed_v4(g_stats + ((i * 8 + j) * 64 + warp * 8 + g), make_uint4(0u, 0u, 0u, 0u));
                    XSTORE(0);
                }
                if (kb == 2) { XSTORE(1); cluster_wait(); }
                if (kb == 3) { XSTORE(2); XSTORE(3); }
                if (kb == 4) { XSTORE(4); XSTORE(5); }
                if (kb == 5) { XSTORE(6); fence_async_smem(); }
                if (kb == 6) { bar_sync(LN_BAR); if (threadIdx.x == 0) TS(0); if (threadIdx.x == 128) TS(58); }
#pragma unroll
                for (int c = 0; c < 28; c += 2) {
                    if (c < (int)((VSCHED >> (8 * kb)) & 255u) || c >= (int)((VSCHED >> (8 * kb + 8)) & 255u)) continue;
                    const uint32_t pa = fma_bf16x2(xf[c + 1][2], xf[c + 1][2], fma_bf16x2(xf[c + 1][0], xf[c + 1][0], fma_bf16x2(xf[c][2], xf[c][2], mul_bf16x2(xf[c][0], xf[c][0]))));
                    const uint32_t pb = fma_bf16x2(xf[c + 1][3], xf[c + 1][3], fma_bf16x2(xf[c + 1][1], xf[c + 1][1], fma_bf16x2(xf[c][3], xf[c][3], mul_bf16x2(xf[c][1], xf[c][1]))));
                    qa += bf_lo(pa); qa2 += bf_hi(pa); qb += bf_lo(pb); qb2 += bf_hi(pb);
                }
                asm volatile("" : "+f"(qa), "+f"(qb), "+f"(qa2), "+f"(qb2));
            }
            rs0 = rsqrtf(fmaxf(quad_sum(qa + qa2) * (1.0f / 448.0f) - dma * dma, 0.f) + 1e-5f);
            rs1 = rsqrtf(fmaxf(quad_sum(qb + qb2) * (1.0f / 448.0f) - dmb * dmb, 0.f) + 1e-5f);
        }
        const GeluC G0 = gelu_consts(rs0), G1 = gelu_consts(rs1);
        epoch = (epoch >> 7) + 1u;
        const uint32_t tag = (epoch % 3u) + 1u;
        uint32_t z2p[28];
        const uint32_t dB_q = dlo(sb + RINGA_OFF, 128);
        {
            float s0 = 0.f, q0 = 0.f, s1 = 0.f, q1 = 0.f;
#pragma unroll
            for (int kb = 0; kb < 7; kb++) {
                wait_full(bars, S_J2 + kb);
                TS2(threadIdx.x == 0, 7 + kb);
                wgmma_fence();
#pragma unroll
                for (int k = 0; k < 4; k++)
                    wgmma_n112<1, HI_SW128, HI_SW128>(acc_b, dA_xn + kb * 1024 + k * 2, dB_ra + wslot(kb + 7) * 1024 + k * 128, (kb | k) != 0);
                wgmma_commit();
                if (kb == 1) { wgmma_wait<2>(); SIGNAL_LOCAL(S_J2 - 1); reg_fence(acc_a); if (threadIdx.x == 0) TS(1); }
                if (kb == 2) { wgmma_wait<1>(); SIGNAL_LOCAL(S_J2); SIGNAL_LOCAL(S_J2 + 1); }
                if (kb >= 3 && kb < 6) { wgmma_wait<1>(); SIGNAL_LOCAL(S_J2 + kb - 1); }
                if (kb == 1 || kb == 2) {
#pragma unroll
                    for (int b = (kb == 1 ? 0 : GSPLIT); b < (kb == 1 ? GSPLIT : 14); b++) {
                        if (b >= 14) continue;
                        const float v0 = gelu_s(acc_a[4 * b], G0), v1 = gelu_s(acc_a[4 * b + 1], G0);
                        const float v2 = gelu_s(acc_a[4 * b + 2], G1), v3 = gelu_s(acc_a[4 * b + 3], G1);
                        s0 += v0 + v1; q0 = fmaf(v0, v0, fmaf(v1, v1, q0));
                        s1 += v2 + v3; q1 = fmaf(v2, v2, fmaf(v3, v3, q1));
                        z2p[2 * b] = pack_bf16(v0, v1); z2p[2 * b + 1] = pack_bf16(v2, v3);
                        asm volatile("" : "+r"(z2p[2 * b]), "+r"(z2p[2 * b + 1]));
                    }
                }
                if (kb == 2) {
                    s0 = quad_sum(s0); q0 = quad_sum(q0); s1 = quad_sum(s1); q1 = quad_sum(q1);
                    if (t == 0) {
                        uint4 pk;
                        pk.x = (__float_as_uint(s0) & ~3u) | tag; pk.y = (__float_as_uint(q0) & ~3u) | tag;
                        pk.z = (__float_as_uint(s1) & ~3u) | tag; pk.w = (__float_as_uint(q1) & ~3u) | tag;
                        st_relaxed_v4(g_stats + ((i * 8 + j) * 64 + warp * 8 + g), pk);
                    }
                    if (threadIdx.x == 0) TS(2);
                }
            }
            wgmma_wait<1>();
            SIGNAL_LOCAL(S_J2 + 5);
        }
        uint32_t z1p[28];
        {
#pragma unroll
            for (int kb = 0; kb < 7; kb++) {
                wait_full(bars, S_J3 + kb);
                TS2(threadIdx.x == 0, 14 + kb);
                wgmma_fence();
#pragma unroll
                for (int k = 0; k < 4; k++)
                    wgmma_n168<1, HI_SW128, hi_sbo(256)>(acc_c, dA_xn + kb * 1024 + k * 2, dB_q + (kb & 3) * (WQ_BYTES >> 4) + k * 336, (kb | k) != 0);
                wgmma_commit();
                if (kb == 1) {
                    if (threadIdx.x == 0) TS(54);
                    mbar_wait(bars + 8 * (B_STATS + wg), 0);
                    wait_done(bars, S_J3 - 1);
                    if (threadIdx.x == 0) TS(3);
                    const uint4 st = lds_v4(sb + STAT_OFF + (warp * 8 + g) * 16);
                    const float r0 = __uint_as_float(st.x), n0 = __uint_as_float(st.y), r1 = __uint_as_float(st.z), n1 = __uint_as_float(st.w);
                    const int m = lane >> 3;
                    const uint32_t sa = sb + Z2S_OFF + (warp * 2 + (m & 1)) * 1792 + ((m >> 1) * 8 + (lane & 7)) * 16;
#pragma unroll
                    for (int b = 0; b < 14; b += 2) {
                        if (b == 8) { wgmma_wait<1>(); SIGNAL_LOCAL(S_J3); asm volatile("" : "+r"(z2p[16]), "+r"(z2p[20]), "+r"(z2p[24])); }
                        stmat_x4_t(sa + b * 128,
                                   pack_bf16(fmaf(bf_lo(z2p[2 * b]), r0, n0), fmaf(bf_hi(z2p[2 * b]), r0, n0)),
                                   pack_bf16(fmaf(bf_lo(z2p[2 * b + 1]), r1, n1), fmaf(bf_hi(z2p[2 * b + 1]), r1, n1)),
                                   pack_bf16(fmaf(bf_lo(z2p[2 * b + 2]), r0, n0), fmaf(bf_hi(z2p[2 * b + 2]), r0, n0)),
                                   pack_bf16(fmaf(bf_lo(z2p[2 * b + 3]), r1, n1), fmaf(bf_hi(z2p[2 * b + 3]), r1, n1)));
                    }
                    fence_async_smem();
                    bar_arrive(3 + wg, 160);
                    if (threadIdx.x == 0) TS(4);
                } else {
                    wgmma_wait<1>();
                    if (kb == 0) SIGNAL_LOCAL(S_J3 - 1); else SIGNAL_DONE(S_J3 + kb - 1);
                }
                if (kb == 0) { reg_fence(acc_b); if (threadIdx.x == 0) TS(5); }
#pragma unroll
                for (int b = 3 * kb - 6; b < 3 * kb - 3; b++) {
                    if (b < 0 || b >= 14) continue;
                    z1p[2 * b] = pack_bf16(gelu_s(acc_b[4 * b], G0), gelu_s(acc_b[4 * b + 1], G0));
                    z1p[2 * b + 1] = pack_bf16(gelu_s(acc_b[4 * b + 2], G1), gelu_s(acc_b[4 * b + 3], G1));
                    asm volatile("" : "+r"(z1p[2 * b]), "+r"(z1p[2 * b + 1]));
                }
            }
        }
        if (threadIdx.x == 0) TS(55);
        const uint32_t dA_g = dlo(sb + wg * 8192, 16);
        const uint32_t dB_g = dlo(sb + 16384, 1792);
        int pos = 1;
        int s = S_G2 + 1;
#define G2_ISSUE() do { \
            wait_full(bars, s); \
            TS3(threadIdx.x == 0, s - S_G2); \
            const uint32_t ro = gstage(pos) >> 4; \
            wgmma_fence(); \
            _Pragma("unroll") \
            for (int k = 0; k < 4; k++) wgmma_n112<0, HI_SW128, HI_NOSW>(acc_a, dA_g + ro + k * 2, dB_g + ro + k * 224, true); \
        } while (0)
#define G2_RETIRE0() do { \
            wgmma_commit(); \
            wgmma_wait<0>(); \
            SIGNAL_DONE(s); \
            pos = pos == 4 ? 0 : pos + 1; \
            s++; \
        } while (0)
#define G2_RETIRE() do { \
            wgmma_commit(); \
            wgmma_wait<1>(); \
            SIGNAL_DONE(s - 1); \
            pos = pos == 4 ? 0 : pos + 1; \
            s++; \
        } while (0)
        {
            wait_full(bars, S_G2);
            if (threadIdx.x == 0) TS(6);
            wgmma_fence();
#pragma unroll
            for (int k = 0; k < 4; k++) wgmma_n112<0, HI_SW128, HI_NOSW>(acc_a, dA_g + k * 2, dB_g + k * 224, k != 0);
            wgmma_commit();
            wgmma_wait<1>();
            SIGNAL_DONE(S_G2 - 1);
            reg_fence(acc_c);
            if (threadIdx.x == 0) TS(7);
            uint32_t pk[42];
#pragma unroll
            for (int b = 7; b < 21; b++) {
                pk[2 * b] = pack_bf16(acc_c[4 * b] * rs0, acc_c[4 * b + 1] * rs0);
                pk[2 * b + 1] = pack_bf16(acc_c[4 * b + 2] * rs1, acc_c[4 * b + 3] * rs1);
                asm volatile("" : "+r"(pk[2 * b]), "+r"(pk[2 * b + 1]));
            }
            if (warp == 7) {
                uint4* hp = g_halo + (size_t)((i * 8 + j) * 14) * 32 + lane;
#pragma unroll
                for (int c = 0; c < 14; c++) st_relaxed_v4(hp + c * 32, make_uint4(pk[14 + 2 * c], epoch, pk[15 + 2 * c], epoch));
            }
            G2_ISSUE();
            G2_RETIRE();
            wait_done(bars, S_J3 + 6);
            const int m = lane >> 3;
            const int r = warp * 16 + (m & 1) * 8 + (lane & 7);
            const uint32_t sk = sb + KV_OFF + (m >> 1) * K_CH + (r & 1) * K_PAR + (16 + (r >> 1)) * 16;
#pragma unroll
            for (int c = 0; c < 14; c += 2) stmat_x4(sk + c * K_CH, pk[14 + 2 * c], pk[15 + 2 * c], pk[16 + 2 * c], pk[17 + 2 * c]);
            G2_ISSUE();
            G2_RETIRE();
            asm volatile("" : "+f"(rs0), "+f"(rs1));
#pragma unroll
            for (int b = 0; b < 7; b++) {
                pk[2 * b] = pack_bf16(acc_c[4 * b] * rs0, acc_c[4 * b + 1] * rs0);
                pk[2 * b + 1] = pack_bf16(acc_c[4 * b + 2] * rs1, acc_c[4 * b + 3] * rs1);
            }
            const uint32_t sq = sb + QQ_OFF + (m >> 1) * Q_CH + (r & 1) * Q_PAR + (r >> 1) * 16;
            stmat_x4(sq, pk[0], pk[1], pk[2], pk[3]);
            stmat_x4(sq + 2 * Q_CH, pk[4], pk[5], t < 2 ? pk[6] : 0u, t < 2 ? pk[7] : 0u);
            stmat_x4(sq + 4 * Q_CH, t < 2 ? 0u : pk[6], t < 2 ? 0u : pk[7], pk[8], pk[9]);
            stmat_x4(sq + 6 * Q_CH, pk[10], pk[11], pk[12], pk[13]);
        }
        wgmma_wait<0>();
        SIGNAL_DONE(s - 1);
#pragma unroll 1
        while (s < S_G2 + ATT_START - 1) { G2_ISSUE(); G2_RETIRE0(); }
        G2_ISSUE();
        wgmma_commit();
        pos = pos == 4 ? 0 : pos + 1;
        s++;
        fence_async_smem();
        bar_sync(6, 288);
        if (threadIdx.x == 0) TS(49);
        const uint32_t bs0 = ld_nc_u16(P.bsp + row0), bs1 = ld_nc_u16(P.bsp + row0 + 8);
        {
            float sc[2][36];
            G2_ISSUE();
#pragma unroll
            for (int e = 0; e < 2; e++) {
                const uint32_t dq = dlo(sb + QQ_OFF + 4 * e * Q_CH + wg * Q_PAR, Q_CH);
                const uint32_t dk = dlo(sb + KV_OFF + 3 * e * K_CH + wg * K_PAR + 128, K_CH);
                wgmma_n72<0, HI_NOSW, HI_NOSW>(sc[e], dq, dk, false);
                wgmma_n72<0, HI_NOSW, HI_NOSW>(sc[e], dq + (2 * Q_CH >> 4), dk + (2 * K_CH >> 4), true);
            }
            G2_RETIRE();
            G2_ISSUE();
            G2_RETIRE();
            reg_fence(sc[0]); reg_fence(sc[1]);
#define BAND(e, k) (w == 0 ? sc[e][k] : w == 1 ? sc[e][8 + k] : w == 2 ? sc[e][16 + k] : sc[e][24 + k])
            const float NEG = __int_as_float(0xff800000);
            const bool c0 = 2 * t > g, c1 = 2 * t + 1 > g;
            const bool first = (i == 0 && w == 0);
            float l[4][4], mx[4];
#pragma unroll
            for (int e = 0; e < 2; e++) {
                l[2 * e][0] = (c0 && !first) ? BAND(e, 0) : NEG;
                l[2 * e][1] = (c1 && !first) ? BAND(e, 1) : NEG;
                l[2 * e][2] = !c0 ? BAND(e, 4) : NEG;
                l[2 * e][3] = !c1 ? BAND(e, 5) : NEG;
                l[2 * e + 1][0] = c0 ? BAND(e, 6) : NEG;
                l[2 * e + 1][1] = c1 ? BAND(e, 7) : NEG;
                l[2 * e + 1][2] = !c0 ? BAND(e, 10) : NEG;
                l[2 * e + 1][3] = !c1 ? BAND(e, 11) : NEG;
            }
#pragma unroll
            for (int r = 0; r < 4; r++) asm volatile("" : "+f"(l[r][0]), "+f"(l[r][1]), "+f"(l[r][2]), "+f"(l[r][3]));
            G2_ISSUE();
            G2_RETIRE();
#pragma unroll
            for (int r = 0; r < 4; r++) {
                asm volatile("" : "+f"(l[r][0]));
                mx[r] = fmaxf(fmaxf(l[r][0], l[r][1]), fmaxf(l[r][2], l[r][3]));
                mx[r] = fmaxf(mx[r], __shfl_xor_sync(0xffffffffu, mx[r], 1));
                mx[r] = fmaxf(mx[r], __shfl_xor_sync(0xffffffffu, mx[r], 2));
                const float scl = 0.18898223650461362f * 1.4426950408889634f;
                const float off = -mx[r] * scl;
#pragma unroll
                for (int k = 0; k < 4; k++) l[r][k] = ex2(fmaf(l[r][k], scl, off));
                asm volatile("" : "+f"(l[r][0]), "+f"(l[r][1]), "+f"(l[r][2]), "+f"(l[r][3]));
            }
            G2_ISSUE();
            G2_RETIRE();
            uint32_t pp[4][2];
#pragma unroll
            for (int r = 0; r < 4; r++) {
                asm volatile("" : "+f"(l[r][0]));
                const float d = __fdividef(1.0f, quad_sum((l[r][0] + l[r][1]) + (l[r][2] + l[r][3])));
                pp[r][0] = pack_bf16(l[r][0] * d, l[r][1] * d); pp[r][1] = pack_bf16(l[r][2] * d, l[r][3] * d);
                asm volatile("" : "+r"(pp[r][0]), "+r"(pp[r][1]));
            }
            G2_ISSUE();
            G2_RETIRE();
            float oc[2][16];
            uint32_t pf[2][5][4];
#pragma unroll
            for (int e = 0; e < 2; e++)
#pragma unroll
                for (int k = 0; k < 5; k++) {
                    asm volatile("" : "+r"(pp[2 * e][0]));
                    pf[e][k][0] = k == w + 1 ? pp[2 * e][1] : 0u; pf[e][k][1] = k == w + 1 ? pp[2 * e + 1][0] : 0u;
                    pf[e][k][2] = k == w ? pp[2 * e][0] : 0u;     pf[e][k][3] = k == w + 1 ? pp[2 * e + 1][1] : 0u;
                    asm volatile("" : "+r"(pf[e][k][0]), "+r"(pf[e][k][1]), "+r"(pf[e][k][2]), "+r"(pf[e][k][3]));
                }
            G2_ISSUE();
#pragma unroll
            for (int e = 0; e < 2; e++) {
                const uint32_t dv = dlo(sb + KV_OFF + (7 + 3 * e) * K_CH + wg * K_PAR, 128);
#pragma unroll
                for (int k = 0; k < 5; k++) wgmma_rs_n32<1, hi_sbo(K_CH)>(oc[e], pf[e][k][0], pf[e][k][1], pf[e][k][2], pf[e][k][3], dv + k * 16, k != 0);
            }
            G2_RETIRE();
            G2_ISSUE();
            G2_RETIRE();
            reg_fence(oc[0]); reg_fence(oc[1]);
            const int m = lane >> 3;
            const uint32_t oa = sb + OS_OFF + (w >> 1) * 7168 + (m >> 1) * 1024 + ((w & 1) * 32 + (m & 1) * 16 + 2 * (lane & 7) + wg) * 16;
#define OPK(e, k) pack_bf16(oc[e][k], oc[e][k + 1])
            stmat_x4(oa, OPK(0, 0), OPK(0, 2), OPK(0, 4), OPK(0, 6));
            stmat_x4(oa + 2048, OPK(0, 8), OPK(0, 10), t < 2 ? OPK(0, 12) : OPK(1, 0), t < 2 ? OPK(0, 14) : OPK(1, 2));
            stmat_x4(oa + 4096, OPK(1, 4), OPK(1, 6), OPK(1, 8), OPK(1, 10));
            stmat_x2(oa + 6144, OPK(1, 12), OPK(1, 14));
        }
        fence_async_smem();
        bar_arrive(11, 320);
        if (threadIdx.x == 0) TS(46);
        wgmma_wait<0>();
        SIGNAL_DONE(s - 1);
        reg_fence(acc_a);
        {
            const float b0 = bf_lo(bs0), b1 = bf_lo(bs1);
#pragma unroll
            for (int b = 0; b < 14; b++) { acc_a[4 * b] += b0; acc_a[4 * b + 1] += b0; acc_a[4 * b + 2] += b1; acc_a[4 * b + 3] += b1; }
        }
        G2_ISSUE();
        wgmma_commit();
        float z1f[56];
#pragma unroll
        for (int b = 0; b < 28; b++) {
            z1f[2 * b] = bf_lo(z1p[b]); z1f[2 * b + 1] = bf_hi(z1p[b]);
            asm volatile("" : "+f"(z1f[2 * b]), "+f"(z1f[2 * b + 1]));
        }
        wgmma_wait<0>();
        SIGNAL_DONE(s);
        pos = pos == 4 ? 0 : pos + 1;
        s++;
#pragma unroll 1
        while (s < S_C - 1) { G2_ISSUE(); G2_RETIRE0(); }
        G2_ISSUE();
        wgmma_commit();
        if (threadIdx.x == 0) TS(13);
        {
            wait_done(bars, S_C - 2);
            const int m = lane >> 3;
            const uint32_t sa = sb + wg * GRAN + (m >> 1) * 1024 + (w * 16 + (m & 1) * 8 + (lane & 7)) * 16;
            wgmma_wait<0>();
            SIGNAL_DONE(S_C - 1);
            reg_fence(acc_a);
            if (threadIdx.x == 0) TS(8);
#pragma unroll
            for (int b = 0; b < 14; b += 2) {
                stmat_x4(sa + b * 1024,
                         pack_bf16(acc_a[4 * b] * z1f[4 * b], acc_a[4 * b + 1] * z1f[4 * b + 1]),
                         pack_bf16(acc_a[4 * b + 2] * z1f[4 * b + 2], acc_a[4 * b + 3] * z1f[4 * b + 3]),
                         pack_bf16(acc_a[4 * b + 4] * z1f[4 * b + 4], acc_a[4 * b + 5] * z1f[4 * b + 5]),
                         pack_bf16(acc_a[4 * b + 6] * z1f[4 * b + 6], acc_a[4 * b + 7] * z1f[4 * b + 7]));
                if (b == USPLIT - 2) { fence_async_smem(); bar_arrive(7, 288); }
            }
            fence_async_smem();
            bar_arrive(8, 288);
            if (threadIdx.x == 0) TS(9);
            bar_sync(1 + wg, 128);
        }
        float acc3[32];
#pragma unroll
        for (int b = 0; b < 8; b++) {
            acc3[4 * b] = bf_lo(xr[2 * b]); acc3[4 * b + 1] = bf_hi(xr[2 * b]);
            acc3[4 * b + 2] = bf_lo(xr[2 * b + 1]); acc3[4 * b + 3] = bf_hi(xr[2 * b + 1]);
        }
        const uint32_t dA_c = dlo(sb + wg * GRAN, 1024);
        const uint32_t dB_c = dlo(sb, 8192);
        {
            uint32_t q = sb + SEL_OFF, heads = 0;
            int n = 0;
#define C_ISSUE() \
                const uint32_t da = dA_c + tail_a_kb(n) * 64, db = dB_c + tail_w_kb(n) * 64; \
                q += 4; \
                int nx = __shfl_sync(0xffffffffu, (int)lds_vol(q), 0); \
                wait_full(bars, S_C + n); \
                if (threadIdx.x == 0) TS(15 + ((q - sb - SEL_OFF) >> 2)); \
                wgmma_fence(); \
                _Pragma("unroll") \
                for (int k = 0; k < 7; k++) wgmma_n64<1, HI_NOSW, HI_SW128>(acc3, da + k * 128, db + k * 128, true); \
                wgmma_commit();
#define C_NEXT() do { uint32_t cnt = 0; while (nx == 0) { nx = __shfl_sync(0xffffffffu, (int)lds_vol(q), 0); SPIN_CHECK2(cnt, 1700) } n = nx; } while (0)
#pragma unroll 1
            while (heads < 2) {
                C_ISSUE();
                wgmma_wait<0>();
                if (n < 7) SIGNAL_DONE(S_C + n);
                heads += (n == 5 || n == 6);
                C_NEXT();
            }
#pragma unroll 1
            while (n < 12) {
                C_ISSUE();
                C_NEXT();
            }
        }
        wgmma_wait<0>();
        reg_fence(acc3);
        if (threadIdx.x == 0) TS(10);
        if (j < 7) {
            bf16* op = P.out + (size_t)row0 * 448 + j * 64 + 8 * t;
#pragma unroll
            for (int hf = 0; hf < 4; hf++) {
                const int bb = (hf & 1) * 4, ro = (hf >> 1) * 2;
                uint32_t v0 = pack_bf16(acc3[4 * bb + ro], acc3[4 * bb + ro + 1]), v1 = pack_bf16(acc3[4 * bb + 4 + ro], acc3[4 * bb + 5 + ro]);
                uint32_t v2 = pack_bf16(acc3[4 * bb + 8 + ro], acc3[4 * bb + 9 + ro]), v3 = pack_bf16(acc3[4 * bb + 12 + ro], acc3[4 * bb + 13 + ro]);
                quad_transpose(v0, v1, v2, v3, t);
                *reinterpret_cast<uint4*>(op + bb * 8 + (hf >> 1) * 8 * 448) = make_uint4(v0, v1, v2, v3);
            }
        }
        if (threadIdx.x == 0) TS(11);
    } else {
        asm volatile("setmaxnreg.dec.sync.aligned.u32 72;");
        bar_sync(9, 384);
        if (threadIdx.x == 256) TS(60);
        if (warp == 8) {
            {
#pragma unroll 1
                for (int n = 0; n < 14; n++) {
                    if (n >= 6) wait_done(bars, n - 6);
                    const uint32_t dst = sb + RINGA_OFF + wslot(n) * 16384;
                    const int col = (n < 7 ? 896 : 0) + j * 112, kb = n < 7 ? n : n - 7;
                    TS2(lane == 0, 32 + n);
                    if (elect_one()) {
                        const uint32_t fb = full_bar(bars, n);
                        mbar_expect_tx(fb, 16384);
                        tma_2d(dst, &P.tm_win, col, kb * 64, fb);
                        tma_2d(dst + 8192, &P.tm_win, col + 64, kb * 64, fb);
                    }
                }
            }
            bar_sync(12, 64);
            fence_async_global();
            cluster_wait();
            {
#define LOAD_WC(n_) do { \
                    const int u_ = (n_); \
                    const bool iso_ = u_ < 5 && u_ != 2; \
                    if (elect_one()) { \
                        const uint32_t fb_ = full_bar(bars, S_C + u_); \
                        mbar_expect_tx(fb_, (u_ == 2 || (u_ == 7 && j == 7) ? 0u : 2 * GRAN) + (j < 7 ? GRAN : 0u)); \
                        if (j < 7) tma_2d(sb + tail_w_kb(u_) * 1024, iso_ ? &P.tm_wo : &P.tm_wout, j * 64, (iso_ ? u_ - (u_ > 2) : tail_src(u_, j)) * 112, fb_); \
                    } \
                } while (0)
                constexpr uint64_t DEP = 0xAA8876653210ull;
                int m = 0, kb = 0, pos = 0;
#pragma unroll 1
                for (int k = 0; k < 39; k++) {
                    wait_done(bars, k < 12 ? 9 + (int)((DEP >> (4 * k)) & 15u) : S_G2 + k - 12);
                    if (k < 8 && k != 6) {
                        TS2(lane == 0, 32 + 14 + m);
                        if (elect_one()) {
                            const uint32_t fb = full_bar(bars, S_J3 + m);
                            mbar_expect_tx(fb, WQ_BYTES);
                            bulk_load(sb + RINGA_OFF + (m & 3) * WQ_BYTES, g_wq + (j * 7 + m) * 1344, WQ_BYTES, fb);
                        }
                        m++;
                    } else {
                        if (kb == 2) mbar_wait(bars + 8 * B_Z2SFREE, 0);
                        TS3(lane == 0, 32 + kb);
                        if (elect_one()) {
                            const uint32_t fb = full_bar(bars, S_G2 + kb);
                            mbar_expect_tx(fb, GBYTES);
                            tma_2d_mc(sb + gstage(pos) + h * 8192, &P.tm_wsp, (kb & 15) * 128 + (kb >> 4) * 64, i * 128 + h * 64, fb);
                        }
                        pos = pos == 4 ? 0 : pos + 1;
                        kb++;

                    }
                }
                mbar_wait(bars + 8 * B_ATTFREE, 0);
                mbar_wait(bars + 8 * B_OREADY, 0);
                fence_async_global();
#pragma unroll 1
                for (int n = 0; n < 12; n++) {
                    int u = n;
                    if (n < 10) wait_done(bars, S_C - 5 + (int)((0x9876542210ull >> (4 * n)) & 15u));
                    if (n == 10) {
                        uint32_t cnt = 0;
                        while (true) {
                            if (mbar_test(done_bar(bars, S_C + 5), ((S_C + 5) >> 4) & 1)) break;
                            if (mbar_test(done_bar(bars, S_C + 6), ((S_C + 6) >> 4) & 1)) { m = 1; break; }
                            SPIN_CHECK2(cnt, 1800)
                        }
                        m = __shfl_sync(0xffffffffu, m == 1, 0);
                    }
                    if (n >= 10) { u = n ^ m; wait_done(bars, S_C + u - 5); }
                    if (n < 5 && n != 2) {
                        if (lane == 0) TS(33 + n);
                        if (elect_one())
                            bulk_load_mc(sb + tail_a_kb(n) * 1024 + h * GRAN, g_ou + (size_t)(i * 2 + h) * 168 * 1024 + (n - (n > 2)) * GRAN, GRAN, full_bar(bars, S_C + n));
                    }
                    LOAD_WC(u);
                }
            }
        } else if (warp == 9) {
            cluster_wait();
            const unsigned tgt = (ld_relaxed(&g_done) >> 7) + 1u;
            {
                wait_done(bars, 0);
                uint32_t cnt = 0;
                while (!__all_sync(0xffffffffu, ld_relaxed(g_wflag + (j * 32 + min(lane, 27)) * 8) == tgt)) { __nanosleep(100); SPIN_CHECK(cnt, 1400) }
                bar_arrive(12, 64);
                if (lane == 0) {
                    TS(59);
                    asm volatile("prefetch.tensormap [%0];" ::"l"(&P.tm_wsp) : "memory");
                    asm volatile("prefetch.tensormap [%0];" ::"l"(&P.tm_wo) : "memory");
                    asm volatile("prefetch.tensormap [%0];" ::"l"(&P.tm_wout) : "memory");
                }
#pragma unroll 1
                for (int r = 0; r < 16; r++) {
                    if (elect_one()) l2_prefetch(reinterpret_cast<const uint8_t*>(P.wsp) + (size_t)blockIdx.x * 65536 + r * 4096, 4096);
                    __nanosleep(PF_SLEEP);
                }
                if (lane == 0) TS(45);
            }
            {
                unsigned ready = 0;
                int pos = 0;
#pragma unroll 1
                for (int kb = 0; kb < 32; kb++) {
                    wait_done(bars, kb >= 5 ? S_G2 + kb - 5 : 10 + (int)((0x99775u >> (4 * kb)) & 15u));
                    if (kb == 2) mbar_wait(bars + 8 * B_Z2SFREE, 0);
                    uint32_t n = 0;
                    while (!((ready >> kb) & 1u)) {
                        ready = __ballot_sync(0xffffffffu, ld_relaxed(g_z2flag + (j * 32 + lane) * 8) == tgt);
                        SPIN_CHECK(n, 1100 + kb)
                        fence_async_global();
                    }
                    if (lane == 0 && kb == 0) TS(32);
                    if (elect_one())
                        bulk_load(sb + gstage(pos) + 16384, g_z2t + (size_t)((kb & 15) * 8 + j) * 28672 + (kb >> 4) * GRAN, GRAN, full_bar(bars, S_G2 + kb));
                    pos = pos == 4 ? 0 : pos + 1;
                }
            }
            {
                const int n = lane == 4 ? 7 : min(lane, 11);
                const int hh = lane == 4 ? h ^ 1 : h;
                const int jt = tail_src(n, j);
                const int dep = S_C - 5 + n;
                const uint32_t dbar = done_bar(bars, dep), dpar = (dep >> 4) & 1;
                const uint32_t xbar = bars + 8 * (n == 7 ? B_USTFREE : B_FULLX);
                const uint32_t dst = sb + tail_a_kb(n) * 1024 + hh * GRAN;
                const uint8_t* sp = g_ou + (size_t)(i * 2 + hh) * 168 * 1024 + (size_t)(4 + jt) * GRAN;
                const uint32_t fb = full_bar(bars, S_C + n);
                bool pending = lane >= 4 && lane < 12 && (j < 7 || n != 7);
                const uint32_t need = 1u << (jt + (hh != h ? 8 : 0));
                uint32_t cnt = 0;
                while (__any_sync(0xffffffffu, pending)) {
                    const bool go = pending && (lds_vol(sb + UFLAG_OFF) & need) && mbar_test(dbar, dpar) && mbar_test(xbar, 0);
                    if (go) {
                        P1_FENCE;
                        TS(33 + n);
                        if (n == 7) bulk_load(dst, sp, GRAN, fb); else bulk_load_mc(dst, sp, GRAN, fb);
                        pending = false;
                    }
                    SPIN_CHECK2(cnt, 1200)
                }
            }
        } else {
            const int a = warp - 10;
            const int hb = i * 2 + a;
            const unsigned tgt = (ld_relaxed(&g_done) >> 7) + 1u;
            if (lane == 0) {
                if (a == 0) l2_prefetch(reinterpret_cast<const uint8_t*>(P.wqkv) + (size_t)blockIdx.x * 9408, 9408);
                else l2_prefetch(reinterpret_cast<const uint8_t*>(P.win) + (size_t)blockIdx.x * 12544, 12544);
            }
            if (lane < 2) {
                const uint4 z = make_uint4(0u, 0u, 0u, 0u);
                st_relaxed_v4(reinterpret_cast<uint4*>(g_wflag + (j * 32 + hb) * 8) + lane, z);
                if (a == 0) {
                    st_relaxed_v4(reinterpret_cast<uint4*>(g_z2flag + (j * 32 + i) * 8) + lane, z);
                    st_relaxed_v4(reinterpret_cast<uint4*>(g_ouflag + (i * 32 + j) * 8) + lane, z);
                    st_relaxed_v4(reinterpret_cast<uint4*>(g_ouflag + (i * 32 + 16 + j) * 8) + lane, z);
                    st_relaxed_v4(reinterpret_cast<uint4*>(g_z2flag + (j * 32 + 16 + i) * 8) + lane, z);
                }
                st_relaxed_v4(reinterpret_cast<uint4*>(g_ouflag + (hb * 16 + 8 + j) * 8) + lane, z);
            }
            const uint32_t rb = bars + 8 * (B_OREADY + 1 + a);
            mbar_wait(bars + 8 * (B_FULLX + 1), 0);
            if (hb < 28) {
                const uint32_t stg = sb + Z2S_OFF + a * 5376;
                if (lane == 0) {
                    mbar_expect_tx(rb, 5376);
#pragma unroll 1
                    for (int q = 0; q < 3; q++) tma_3d(stg + q * 1792, &P.tm_wqkv, 0, hb * 16, q * 56 + j * 7, rb);
                }
                __syncwarp();
                mbar_wait(rb, 0);
                if (lane == 0) {
                    bulk_store(g_wq + (j * 28 + hb) * 336, stg, 5376);
                    asm volatile("cp.async.bulk.wait_group 0;" ::: "memory");
                    PUBLISH(g_wflag + (j * 32 + hb) * 8, tgt);
                    if (a == 0) TS(61);
                }
            }
            if (lane == 0) {
                if (a == 0) l2_prefetch(reinterpret_cast<const uint8_t*>(P.wo) + (size_t)blockIdx.x * 3136, 3136);
                else l2_prefetch(reinterpret_cast<const uint8_t*>(P.wout) + (size_t)blockIdx.x * 6272, 6272);
            }
            __syncwarp();
            cluster_wait();
            {
                const uint32_t tag = (tgt % 3u) + 1u;
                const uint4* sp = g_stats + (i * 8 * 64 + a * 32 + lane);
                wait_done(bars, S_J2 + 1);
                float S0, Q0, S1, Q1;
                uint32_t n = 0;
                while (true) {
                    uint4 p[8];
#pragma unroll
                    for (int c = 0; c < 8; c++) p[c] = ld_relaxed_v4(sp + c * 64);
                    uint32_t all = 3u, any = 0u;
                    S0 = Q0 = S1 = Q1 = 0.f;
#pragma unroll
                    for (int c = 0; c < 8; c++) {
                        all &= p[c].x & p[c].y & p[c].z & p[c].w; any |= p[c].x | p[c].y | p[c].z | p[c].w;
                        S0 += __uint_as_float(p[c].x); Q0 += __uint_as_float(p[c].y); S1 += __uint_as_float(p[c].z); Q1 += __uint_as_float(p[c].w);
                    }
                    if (__all_sync(0xffffffffu, all == tag && (any & 3u) == tag)) break;
                    SPIN_CHECK(n, 1000)
                }
                const float m0 = S0 * (1.0f / 896.0f), m1 = S1 * (1.0f / 896.0f);
                const float r0 = rsqrtf(fmaxf(Q0 * (1.0f / 896.0f) - m0 * m0, 0.f) + 1e-5f);
                const float r1 = rsqrtf(fmaxf(Q1 * (1.0f / 896.0f) - m1 * m1, 0.f) + 1e-5f);
                sts_v4(sb + STAT_OFF + (a * 32 + lane) * 16, make_uint4(__float_as_uint(r0), __float_as_uint(-m0 * r0), __float_as_uint(r1), __float_as_uint(-m1 * r1)));
                __syncwarp();
                if (lane == 0) mbar_arrive(bars + 8 * (B_STATS + a));
            }
            if (a == 0) {
                uint8_t* dst = g_z2t + (size_t)(i * 8 + j) * 28672;
                bar_sync(3, 160);
                if (lane == 0) {
                    bulk_store(dst, sb + Z2S_OFF, 7168);
                    asm volatile("cp.async.bulk.wait_group.read 0;" ::: "memory");
                    bulk_store(dst + 7168, sb + Z2S_OFF + 7168, 7168);
                    asm volatile("cp.async.bulk.wait_group.read 0;" ::: "memory");
                }
                __syncwarp();
                bar_sync(4, 160);
                if (lane == 0) {
                    bulk_store(dst + GRAN, sb + Z2S_OFF + GRAN, 7168);
                    asm volatile("cp.async.bulk.wait_group 1;" ::: "memory");
                    PUBLISH(g_z2flag + (j * 32 + i) * 8, tgt);
                    TS(47);
                    asm volatile("cp.async.bulk.wait_group.read 0;" ::: "memory");
                    bulk_store(dst + GRAN + 7168, sb + Z2S_OFF + GRAN + 7168, 7168);
                    asm volatile("cp.async.bulk.wait_group 0;" ::: "memory");
                    PUBLISH(g_z2flag + (j * 32 + 16 + i) * 8, tgt);
                    mbar_arrive(bars + 8 * B_Z2SFREE);
                    mbar_arrive_remote(bars + 8 * B_Z2SFREE, h ^ 1);
                    TS(48);
                }
                __syncwarp();
            }
            if (a == 0) {
                wait_done(bars, S_G2);
                uint4 hv[14];
                if (i > 0) {
                    const uint4* hp = g_halo + (size_t)(((i - 1) * 8 + j) * 14) * 32 + lane;
                    uint32_t n = 0;
                    while (true) {
                        bool ok = true;
#pragma unroll
                        for (int c = 0; c < 14; c++) hv[c] = ld_relaxed_v4(hp + c * 32);
#pragma unroll
                        for (int c = 0; c < 14; c++) ok = ok && hv[c].y == tgt && hv[c].w == tgt;
                        if (__all_sync(0xffffffffu, ok)) break;
                        POLL_SLEEP;
                        SPIN_CHECK(n, 1300)
                    }
                } else {
#pragma unroll
                    for (int c = 0; c < 14; c++) hv[c] = make_uint4(0u, 0u, 0u, 0u);
                }
                const int m = lane >> 3;
                const int r = (m & 1) * 8 + (lane & 7);
                const uint32_t sa = sb + KV_OFF + (m >> 1) * K_CH + (r & 1) * K_PAR + (r >> 1) * 16;
#pragma unroll
                for (int c = 0; c < 14; c += 2) {
                    stmat_x4(sa + c * K_CH + 128, hv[c].x, hv[c].z, hv[c + 1].x, hv[c + 1].z);
                    if (c >= 6) stmat_x4(sa + c * K_CH, 0u, 0u, 0u, 0u);
                }
                fence_async_smem();
                bar_arrive(6, 288);
                if (lane == 0) TS(50);
            }
            bar_sync(11, 320);
            if (lane == 0) {
                bulk_store(g_ou + ((size_t)hb * 168 + 7 * j) * 1024, sb + OS_OFF + a * 7168, 7168);
                asm volatile("cp.async.bulk.wait_group 0;" ::: "memory");
                PUBLISH(g_ouflag + (hb * 16 + 8 + j) * 8, tgt);
                mbar_arrive(bars + 8 * B_ATTFREE);
                if (a == 0) TS(51);
            }
            __syncwarp();
            if (a == 1) {
                uint32_t cnt = 0;
                while (!__all_sync(0xffffffffu, ld_relaxed(g_ouflag + ((i * 2 + h) * 16 + 8 + (lane & 7)) * 8) == tgt)) { POLL_SLEEP; SPIN_CHECK(cnt, 1500) }
                fence_async_global();
                if (lane == 0) { mbar_arrive(bars + 8 * B_OREADY); TS(62); }
                __syncwarp();
            }
            if (a == 0) {
                uint8_t* dst = g_ou + ((size_t)i * 2 * 168 + 56 + 14 * j) * 1024;
                bar_sync(7, 288);
                if (lane == 0) {
                    bulk_store(dst, sb, USPLIT * 1024);
                    bulk_store(dst + 168 * 1024, sb + GRAN, USPLIT * 1024);
                }
                __syncwarp();
                bar_sync(8, 288);
                if (lane == 0) {
                    bulk_store(dst + USPLIT * 1024, sb + USPLIT * 1024, GRAN - USPLIT * 1024);
                    bulk_store(dst + (168 + USPLIT) * 1024, sb + GRAN + USPLIT * 1024, GRAN - USPLIT * 1024);
                    asm volatile("cp.async.bulk.wait_group 1;" ::: "memory");
                    PUBLISH(UFLAG(i * 2, j), tgt);
                    asm volatile("cp.async.bulk.wait_group 0;" ::: "memory");
                    PUBLISH(UFLAG(i * 2 + 1, j), tgt);
                    mbar_arrive(bars + 8 * B_USTFREE);
                    mbar_arrive_remote(bars + 8 * B_USTFREE, h ^ 1);
                    atomicAdd(&g_done, 1u);
                    TS(52);
                }
                __syncwarp();
                bool pending = lane >= 5 && lane < 12;
                const uint32_t mybar = full_bar(bars, S_C + lane), mypar = ((S_C + lane) >> 4) & 1;
                uint32_t q = sb + SEL_OFF + 20, cnt = 0;
                while (q != sb + SEL_OFF + 48) {
                    const bool go = pending && mbar_test(mybar, mypar);
                    const uint32_t rdy = __ballot_sync(0xffffffffu, go);
                    if (go) { sts_vol(q + 4 * __popc(rdy & ((1u << lane) - 1u)), (uint32_t)lane); pending = false; }
                    q += 4 * __popc(rdy);
                    SPIN_CHECK2(cnt, 1900)
                }
            } else {
                wait_done(bars, S_C - 3);
                const unsigned* fp = UFLAG(i * 2 + (h ^ ((lane >> 3) & 1)), lane & 7);
                uint32_t cnt = 0, mask = ~((0xffu & ~(1u << j)) | (0x100u << (j ^ 1)));
                while (mask != 0xffffffffu) {
                    unsigned v = 0;
                    if (!((mask >> lane) & 1u)) v = ld_relaxed(fp);
                    mask |= __ballot_sync(0xffffffffu, v == tgt);
                    AUX_FENCE;
                    if (lane == 0) sts_vol(sb + UFLAG_OFF, mask);
                    SPIN_CHECK(cnt, 1600)
                }
                if (lane == 0) { TS(30); }
            }
        }
    }
}

typedef CUresult (*PFN_encodeTiled)(CUtensorMap*, CUtensorMapDataType, cuuint32_t, void*, const cuuint64_t*, const cuuint64_t*,
                                    const cuuint32_t*, const cuuint32_t*, CUtensorMapInterleave, CUtensorMapSwizzle,
                                    CUtensorMapL2promotion, CUtensorMapFloatOOBfill);

void make_map(PFN_encodeTiled enc, CUtensorMap* tm, const void* ptr, int rank, const cuuint64_t* dims, const cuuint64_t* strides,
              const cuuint32_t* box, CUtensorMapSwizzle sw) {
    cuuint32_t es[3] = {1, 1, 1};
    enc(tm, CU_TENSOR_MAP_DATA_TYPE_BFLOAT16, rank, const_cast<void*>(ptr), dims, strides, box, es, CU_TENSOR_MAP_INTERLEAVE_NONE,
        sw, L2PROMO, CU_TENSOR_MAP_FLOAT_OOB_FILL_NONE);
}

}

extern "C" void kernel_launch(void* const* d_in, const int* in_sizes, int n_in, void* d_out, int out_size) {
    (void)in_sizes; (void)n_in; (void)out_size;
    PFN_encodeTiled enc = nullptr;
    cudaDriverEntryPointQueryResult st;
    cudaGetDriverEntryPoint("cuTensorMapEncodeTiled", (void**)&enc, cudaEnableDefault, &st);
    Params P;
    P.x = (const bf16*)d_in[0];
    P.wqkv = (const bf16*)d_in[1];
    P.wo = (const bf16*)d_in[2];
    P.win = (const bf16*)d_in[4];
    P.wsp = (const bf16*)d_in[5];
    P.bsp = (const bf16*)d_in[6];
    P.wout = (const bf16*)d_in[7];
    P.out = (bf16*)d_out;
    {
        cuuint64_t d[2] = {1792, 448}, s[1] = {3584}; cuuint32_t b[2] = {64, 64};
        make_map(enc, &P.tm_win, P.win, 2, d, s, b, CU_TENSOR_MAP_SWIZZLE_128B);
    }
    {
        cuuint64_t d[2] = {448, 2048}, s[1] = {896}; cuuint32_t b[2] = {64, 64};
        make_map(enc, &P.tm_x, P.x, 2, d, s, b, CU_TENSOR_MAP_SWIZZLE_128B);
    }
    {
        cuuint64_t d[2] = {2048, 2048}, s[1] = {4096}; cuuint32_t b[2] = {64, 64};
        make_map(enc, &P.tm_wsp, P.wsp, 2, d, s, b, CU_TENSOR_MAP_SWIZZLE_128B);
    }
    {
        cuuint32_t b[3] = {8, 16, 7};
        cuuint64_t d0[3] = {8, 448, 168}, s0[2] = {2688, 16};
        make_map(enc, &P.tm_wqkv, P.wqkv, 3, d0, s0, b, CU_TENSOR_MAP_SWIZZLE_NONE);
        cuuint32_t bw[2] = {64, 112};
        cuuint64_t d1[2] = {448, 448}, s1[1] = {896};
        make_map(enc, &P.tm_wo, P.wo, 2, d1, s1, bw, CU_TENSOR_MAP_SWIZZLE_128B);
        cuuint64_t d2[2] = {448, 896};
        make_map(enc, &P.tm_wout, P.wout, 2, d2, s1, bw, CU_TENSOR_MAP_SWIZZLE_128B);
    }
    cudaFuncSetAttribute(fused_kernel, cudaFuncAttributeMaxDynamicSharedMemorySize, SMEM_BYTES);
    fused_kernel<<<128, 384, SMEM_BYTES>>>(P);
}
```

```cpp
#include <cuda_runtime.h>
#include <cuda_bf16.h>
#include <cuda.h>
#include <stdint.h>

#define NATT 2
#define P1_FENCE do {} while (0)
#define AUX_FENCE fence_async_global()
#define W0_POST 1
#define W0_PRE 1
#define USPLIT 6
#define PSTAG 150
#define UFLAG(hb, j) (g_ouflag + ((hb) * 16 + (j)) * 8)
#define G2K 4
#define KROT 0
#define ZNEED (kb < 16 ? 0xffffu : 0xffffffffu)
#define TICKB 0
#define PACE 575
#define PACE2 575
#define PACE3 575
#define PACE0 700
#define STAMP 0
#define WINA 0
#define WINB 0
#define STAMP0 300
#define NSPLIT 14
#define Z2ONE 0
#define PK1 12
#define PK2 21
#define TICKA 0
#define TICKQ 256u
#define TICKW 64u
#define POLL_SLEEP do {} while (0)
#define PF_SLEEP 120
#define Z2PIECES 2
#define LN_BAR 1 + wg, 128
#define GSPLIT 8
#define NORM_KB 0
#define Z1SCHED 0xECA86300u
#define ATT_START 9
#define L2PROMO CU_TENSOR_MAP_L2_PROMOTION_L2_128B
namespace {

typedef __nv_bfloat16 bf16;

__device__ __align__(1024) uint8_t g_z2t[16 * 8 * 28672];
__device__ __align__(1024) uint8_t g_ou[16 * 2 * 168 * 1024];
__device__ __align__(1024) uint4 g_wq[8 * 28 * 21 * 16];
__device__ __align__(128) unsigned g_wflag[8 * 32 * 8];
__device__ __align__(128) uint4 g_halo[16 * 8 * 14 * 32];
__device__ __align__(128) uint4 g_stats[16 * 8 * 64];
__device__ __align__(128) unsigned g_z2flag[8 * 32 * 8];
__device__ __align__(128) unsigned g_ouflag[32 * 16 * 8];
__device__ unsigned g_done;
#define TS3(c, k) do {} while (0)
#define TS2(c, k) do {} while (0)
#define TS(k) do {} while (0)
#define SPIN_CHECK(n, code) if (++n > (1u << 20)) __trap();
#define SPIN_CHECK2(n, code) if (++n > (1u << 24)) __trap();

constexpr uint32_t XN_OFF = 0;
constexpr uint32_t RINGA_OFF = 114688;
constexpr uint32_t Z2S_OFF = 200704;
constexpr uint32_t GBYTES = 30720;
constexpr uint64_t GSTAGE_KB = 0x703CC21E00ull;
constexpr uint32_t GRAN = 14336;
constexpr uint32_t WQ_BYTES = 21504;
constexpr uint32_t QQ_OFF = 92160, Q_PAR = 1088, Q_CH = 2176;
constexpr uint32_t KV_OFF = 145408, K_PAR = 1344, K_CH = 2688;
constexpr uint32_t OS_OFF = KV_OFF + 14 * K_CH;
static_assert(QQ_OFF + 8 * Q_CH <= 114688 && OS_OFF + 14336 <= 198656, "smem");
constexpr uint32_t BAR_OFF = 229376;
constexpr int B_FULL = 0, B_DONE = 16, B_FULLX = 32, B_Z2SFREE = 34, B_ATTFREE = 35, B_USTFREE = 36, B_OREADY = 37, B_STATS = 40, NBARS = 42;
constexpr int S_J2 = 7, S_J3 = 14, S_G2 = 21, S_C = 53;
constexpr uint32_t UFLAG_OFF = BAR_OFF + 384;
constexpr uint32_t STAT_OFF = BAR_OFF + 1024;
constexpr uint32_t SMEM_BYTES = BAR_OFF + 2048 + 1024;
__device__ __forceinline__ uint32_t slot_a_kb(int sl) { return (uint32_t)(0x1E70003CC4ull >> (8 * sl)) & 255u; }
__device__ __forceinline__ uint32_t slot_w_kb(int sl) { return (uint32_t)(0x5AB68CA89Aull >> (8 * sl)) & 255u; }
__device__ __forceinline__ int tail_src(int n, int j) {
    return n == 2 ? j : n == 7 ? j ^ 1 : ((j & 6) + (int)((0x537604200000ull >> (4 * n)) & 15u)) & 7;
}
constexpr uint32_t SEL_OFF = BAR_OFF + 400;

__device__ __forceinline__ uint32_t smem_u32(const void* p) { return (uint32_t)__cvta_generic_to_shared(p); }
__device__ __forceinline__ void mbar_init(uint32_t bar, uint32_t count) {
    asm volatile("mbarrier.init.shared::cta.b64 [%0], %1;" ::"r"(bar), "r"(count) : "memory");
}
__device__ __forceinline__ void mbar_expect_tx(uint32_t bar, uint32_t bytes) {
    asm volatile("mbarrier.arrive.expect_tx.shared::cta.b64 _, [%0], %1;" ::"r"(bar), "r"(bytes) : "memory");
}
__device__ __forceinline__ void mbar_arrive(uint32_t bar) {
    asm volatile("mbarrier.arrive.shared::cta.b64 _, [%0];" ::"r"(bar) : "memory");
}
__device__ __forceinline__ void mbar_arrive_remote(uint32_t bar, uint32_t cta) {
    asm volatile("{\n.reg .b32 ra;\nmapa.shared::cluster.u32 ra, %0, %1;\nmbarrier.arrive.shared::cluster.b64 _, [ra];\n}\n" ::"r"(bar), "r"(cta) : "memory");
}
__device__ __forceinline__ void mbar_wait(uint32_t bar, uint32_t par) {
    asm volatile("{\n.reg .pred p;\n.reg .u32 n;\nmov.u32 n, 0;\n"
                 "W_LOOP:\nmbarrier.try_wait.parity.shared::cta.b64 p, [%0], %1;\n@p bra W_DONE;\n"
                 "add.u32 n, n, 1;\nsetp.lt.u32 p, n, 0x100000;\n@p bra W_LOOP;\ntrap;\nW_DONE:\n}\n" ::"r"(bar), "r"(par) : "memory");
}
__device__ __forceinline__ bool mbar_test(uint32_t bar, uint32_t par) {
    uint32_t ok;
    asm volatile("{\n.reg .pred p;\nmbarrier.test_wait.parity.shared::cta.b64 p, [%1], %2;\nselp.u32 %0, 1, 0, p;\n}\n" : "=r"(ok) : "r"(bar), "r"(par) : "memory");
    return ok != 0;
}
__host__ __device__ constexpr uint32_t wslot(int n) { return (uint32_t)(0x64321064321064ull >> (4 * n)) & 15u; }
__device__ __forceinline__ uint32_t gstage(int pos) { return ((uint32_t)(GSTAGE_KB >> (8 * pos)) & 255u) << 10; }
__device__ __forceinline__ uint32_t lds_u32(uint32_t a) {
    uint32_t v; asm volatile("ld.shared.u32 %0, [%1];" : "=r"(v) : "r"(a) : "memory"); return v;
}
__device__ __forceinline__ uint32_t lds_vol(uint32_t a) {
    uint32_t v; asm volatile("ld.volatile.shared.u32 %0, [%1];" : "=r"(v) : "r"(a) : "memory"); return v;
}
__device__ __forceinline__ void sts_vol(uint32_t a, uint32_t v) { asm volatile("st.volatile.shared.u32 [%0], %1;" ::"r"(a), "r"(v) : "memory"); }
__device__ __forceinline__ uint32_t full_bar(uint32_t bars, int step) { return bars + 8 * (B_FULL + (step & 15)); }
__device__ __forceinline__ uint32_t done_bar(uint32_t bars, int step) { return bars + 8 * (B_DONE + (step & 15)); }
__device__ __forceinline__ void wait_full(uint32_t bars, int step) { mbar_wait(full_bar(bars, step), (step >> 4) & 1); }
__device__ __forceinline__ void wait_done(uint32_t bars, int step) { mbar_wait(done_bar(bars, step), (step >> 4) & 1); }
__device__ __forceinline__ void tma_3d(uint32_t dst, const CUtensorMap* tm, int c0, int c1, int c2, uint32_t bar) {
    asm volatile("cp.async.bulk.tensor.3d.shared::cluster.global.mbarrier::complete_tx::bytes [%0], [%1, {%3, %4, %5}], [%2];"
                 ::"r"(dst), "l"(tm), "r"(bar), "r"(c0), "r"(c1), "r"(c2) : "memory");
}
__device__ __forceinline__ void tma_2d(uint32_t dst, const CUtensorMap* tm, int c0, int c1, uint32_t bar) {
    asm volatile("cp.async.bulk.tensor.2d.shared::cluster.global.mbarrier::complete_tx::bytes [%0], [%1, {%3, %4}], [%2];"
                 ::"r"(dst), "l"(tm), "r"(bar), "r"(c0), "r"(c1) : "memory");
}
__device__ __forceinline__ void tma_2d_mc(uint32_t dst, const CUtensorMap* tm, int c0, int c1, uint32_t bar) {
    asm volatile("cp.async.bulk.tensor.2d.shared::cluster.global.mbarrier::complete_tx::bytes.multicast::cluster [%0], [%1, {%3, %4}], [%2], %5;"
                 ::"r"(dst), "l"(tm), "r"(bar), "r"(c0), "r"(c1), "h"((uint16_t)3) : "memory");
}
__device__ __forceinline__ void bulk_load(uint32_t dst, const void* src, uint32_t bytes, uint32_t bar) {
    asm volatile("cp.async.bulk.shared::cluster.global.mbarrier::complete_tx::bytes [%0], [%1], %2, [%3];"
                 ::"r"(dst), "l"(src), "r"(bytes), "r"(bar) : "memory");
}
__device__ __forceinline__ void bulk_load_mc(uint32_t dst, const void* src, uint32_t bytes, uint32_t bar) {
    asm volatile("cp.async.bulk.shared::cluster.global.mbarrier::complete_tx::bytes.multicast::cluster [%0], [%1], %2, [%3], %4;"
                 ::"r"(dst), "l"(src), "r"(bytes), "r"(bar), "h"((uint16_t)3) : "memory");
}
__device__ __forceinline__ void bulk_store(void* dst, uint32_t src, uint32_t bytes) {
    asm volatile("cp.async.bulk.global.shared::cta.bulk_group [%0], [%1], %2;" ::"l"(dst), "r"(src), "r"(bytes) : "memory");
    asm volatile("cp.async.bulk.commit_group;" ::: "memory");
}
__device__ __forceinline__ void l2_prefetch(const void* p, uint32_t bytes) {
    asm volatile("cp.async.bulk.prefetch.L2.global [%0], %1;" ::"l"(p), "r"(bytes) : "memory");
}
__device__ __forceinline__ void wgmma_fence() { asm volatile("wgmma.fence.sync.aligned;" ::: "memory"); }
__device__ __forceinline__ void wgmma_commit() { asm volatile("wgmma.commit_group.sync.aligned;" ::: "memory"); }
template <int N> __device__ __forceinline__ void wgmma_wait() { asm volatile("wgmma.wait_group.sync.aligned %0;" ::"n"(N) : "memory"); }
template <int N> __device__ __forceinline__ void reg_fence(float (&d)[N]) {
#pragma unroll
    for (int k = 0; k < N; k++) asm volatile("" : "+f"(d[k])::"memory");
}
__device__ __forceinline__ uint32_t dlo(uint32_t addr, uint32_t lbo) { return ((addr & 0x3FFFF) >> 4) | ((lbo >> 4) << 16); }
constexpr uint32_t HI_SW128 = (1024 >> 4) | (1u << 30);
constexpr uint32_t HI_NOSW = (128 >> 4);
#define hi_sbo(sbo) ((sbo) / 16)
__device__ __forceinline__ void bar_sync(int id, int n) { asm volatile("bar.sync %0, %1;" ::"r"(id), "r"(n) : "memory"); }
__device__ __forceinline__ void bar_arrive(int id, int n) { asm volatile("bar.arrive %0, %1;" ::"r"(id), "r"(n) : "memory"); }
__device__ __forceinline__ void fence_async_smem() { asm volatile("fence.proxy.async.shared::cta;" ::: "memory"); }
__device__ __forceinline__ void fence_async_global() { asm volatile("fence.proxy.async.global;" ::: "memory"); }
__device__ __forceinline__ void cluster_arrive() { asm volatile("barrier.cluster.arrive.release.aligned;" ::: "memory"); }
__device__ __forceinline__ void cluster_arrive_relaxed() { asm volatile("barrier.cluster.arrive.relaxed.aligned;" ::: "memory"); }
__device__ __forceinline__ void mbar_arrive_cl(uint32_t cluster_addr) {
    asm volatile("mbarrier.arrive.shared::cluster.b64 _, [%0];" ::"r"(cluster_addr) : "memory");
}
__device__ __forceinline__ bool elect_one() {
    uint32_t p;
    asm volatile("{\n.reg .pred q;\nelect.sync _|q, 0xffffffff;\nselp.u32 %0, 1, 0, q;\n}\n" : "=r"(p));
    return p != 0;
}
__device__ __forceinline__ void cluster_wait() { asm volatile("barrier.cluster.wait.acquire.aligned;" ::: "memory"); }
__device__ __forceinline__ unsigned ld_acquire(const unsigned* p) {
    unsigned v; asm volatile("ld.acquire.gpu.global.u32 %0, [%1];" : "=r"(v) : "l"(p) : "memory"); return v;
}
__device__ __forceinline__ void st_release(unsigned* p, unsigned v) {
    asm volatile("st.release.gpu.global.u32 [%0], %1;" ::"l"(p), "r"(v) : "memory");
}
__device__ __forceinline__ void st_relaxed(unsigned* p, unsigned v) {
    asm volatile("st.relaxed.gpu.global.u32 [%0], %1;" ::"l"(p), "r"(v) : "memory");
}
__device__ __forceinline__ uint4 ld_relaxed_v4(const uint4* p) {
    uint4 v; asm volatile("ld.relaxed.gpu.global.v4.u32 {%0,%1,%2,%3}, [%4];" : "=r"(v.x), "=r"(v.y), "=r"(v.z), "=r"(v.w) : "l"(p) : "memory"); return v;
}
__device__ __forceinline__ void st_relaxed_v4(uint4* p, uint4 v) {
    asm volatile("st.relaxed.gpu.global.v4.u32 [%0], {%1,%2,%3,%4};" ::"l"(p), "r"(v.x), "r"(v.y), "r"(v.z), "r"(v.w) : "memory");
}
__device__ __forceinline__ uint4 ld_nc_v4(const void* p) {
    uint4 v; asm volatile("ld.global.nc.v4.u32 {%0,%1,%2,%3}, [%4];" : "=r"(v.x), "=r"(v.y), "=r"(v.z), "=r"(v.w) : "l"(p)); return v;
}
__device__ __forceinline__ uint4 ld_v4(const void* p) {
    uint4 v; asm volatile("ld.global.v4.u32 {%0,%1,%2,%3}, [%4];" : "=r"(v.x), "=r"(v.y), "=r"(v.z), "=r"(v.w) : "l"(p) : "memory"); return v;
}
__device__ __forceinline__ uint4 lds_v4(uint32_t a) {
    uint4 v; asm volatile("ld.shared.v4.u32 {%0,%1,%2,%3}, [%4];" : "=r"(v.x), "=r"(v.y), "=r"(v.z), "=r"(v.w) : "r"(a) : "memory"); return v;
}
__device__ __forceinline__ unsigned ld_relaxed(const unsigned* p) {
    unsigned v; asm volatile("ld.relaxed.gpu.global.u32 %0, [%1];" : "=r"(v) : "l"(p) : "memory"); return v;
}
__device__ __forceinline__ uint2 ld_relaxed_v2(const unsigned* p) {
    uint2 v; asm volatile("ld.relaxed.gpu.global.v2.u32 {%0, %1}, [%2];" : "=r"(v.x), "=r"(v.y) : "l"(p) : "memory"); return v;
}
__device__ __forceinline__ void st_relaxed_v2(unsigned* p, unsigned a, unsigned b) {
    asm volatile("st.relaxed.gpu.global.v2.u32 [%0], {%1, %2};" ::"l"(p), "r"(a), "r"(b) : "memory");
}
__device__ __forceinline__ unsigned gtimer() { unsigned t; asm volatile("mov.u32 %0, %%globaltimer_lo;" : "=r"(t)); return t; }
__device__ __forceinline__ void sts_u32(uint32_t a, uint32_t v) { asm volatile("st.shared.u32 [%0], %1;" ::"r"(a), "r"(v) : "memory"); }
__device__ __forceinline__ void sts_v4(uint32_t a, uint4 v) {
    asm volatile("st.shared.v4.u32 [%0], {%1,%2,%3,%4};" ::"r"(a), "r"(v.x), "r"(v.y), "r"(v.z), "r"(v.w) : "memory");
}
__device__ __forceinline__ uint32_t pack_bf16(float lo, float hi) {
    uint32_t r; asm("cvt.rn.bf16x2.f32 %0, %1, %2;" : "=r"(r) : "f"(hi), "f"(lo)); return r;
}
__device__ __forceinline__ float bf_lo(uint32_t r) { return __uint_as_float(r << 16); }
__device__ __forceinline__ float bf_hi(uint32_t r) { return __uint_as_float(r & 0xffff0000u); }
__device__ __forceinline__ void unpack8(float (&f)[8], uint4 v) {
    f[0] = bf_lo(v.x); f[1] = bf_hi(v.x); f[2] = bf_lo(v.y); f[3] = bf_hi(v.y);
    f[4] = bf_lo(v.z); f[5] = bf_hi(v.z); f[6] = bf_lo(v.w); f[7] = bf_hi(v.w);
}
__device__ __forceinline__ uint32_t ld_nc_u32(const void* p) {
    uint32_t v; asm volatile("ld.global.nc.u32 %0, [%1];" : "=r"(v) : "l"(p)); return v;
}
__device__ __forceinline__ uint32_t ld_nc_u16(const void* p) {
    uint16_t v; asm volatile("ld.global.nc.u16 %0, [%1];" : "=h"(v) : "l"(p)); return v;
}
__device__ __forceinline__ uint32_t mul_bf16x2(uint32_t a, uint32_t b) {
    uint32_t r; asm("mul.rn.bf16x2 %0, %1, %2;" : "=r"(r) : "r"(a), "r"(b)); return r;
}
__device__ __forceinline__ uint32_t fma_bf16x2(uint32_t a, uint32_t b, uint32_t c) {
    uint32_t r; asm("fma.rn.bf16x2 %0, %1, %2, %3;" : "=r"(r) : "r"(a), "r"(b), "r"(c)); return r;
}
__device__ __forceinline__ uint32_t sub_bf16x2(uint32_t a, uint32_t b) {
    uint32_t r; asm("sub.rn.bf16x2 %0, %1, %2;" : "=r"(r) : "r"(a), "r"(b)); return r;
}
__device__ __forceinline__ void mma16816(float (&c)[4], uint32_t a0, uint32_t a1, uint32_t a2, uint32_t a3, uint32_t b0, uint32_t b1) {
    asm("mma.sync.aligned.m16n8k16.row.col.f32.bf16.bf16.f32 {%0,%1,%2,%3}, {%4,%5,%6,%7}, {%8,%9}, {%0,%1,%2,%3};"
        : "+f"(c[0]), "+f"(c[1]), "+f"(c[2]), "+f"(c[3]) : "r"(a0), "r"(a1), "r"(a2), "r"(a3), "r"(b0), "r"(b1));
}
__device__ __forceinline__ void mma1688(float (&c)[4], uint32_t a0, uint32_t a1, uint32_t b0) {
    asm volatile("mma.sync.aligned.m16n8k8.row.col.f32.bf16.bf16.f32 {%0,%1,%2,%3}, {%4,%5}, {%6}, {%0,%1,%2,%3};"
        : "+f"(c[0]), "+f"(c[1]), "+f"(c[2]), "+f"(c[3]) : "r"(a0), "r"(a1), "r"(b0));
}
__device__ __forceinline__ uint32_t movmat(uint32_t a) {
    uint32_t d; asm("movmatrix.sync.aligned.m8n8.trans.b16 %0, %1;" : "=r"(d) : "r"(a)); return d;
}
__device__ __forceinline__ void ldmat_x4(uint32_t& r0, uint32_t& r1, uint32_t& r2, uint32_t& r3, uint32_t a) {
    asm volatile("ldmatrix.sync.aligned.m8n8.x4.shared.b16 {%0,%1,%2,%3}, [%4];" : "=r"(r0), "=r"(r1), "=r"(r2), "=r"(r3) : "r"(a) : "memory");
}
__device__ __forceinline__ void stmat_x4(uint32_t a, uint32_t r0, uint32_t r1, uint32_t r2, uint32_t r3) {
    asm volatile("stmatrix.sync.aligned.m8n8.x4.shared.b16 [%0], {%1,%2,%3,%4};" ::"r"(a), "r"(r0), "r"(r1), "r"(r2), "r"(r3) : "memory");
}
__device__ __forceinline__ void stmat_x2(uint32_t a, uint32_t r0, uint32_t r1) {
    asm volatile("stmatrix.sync.aligned.m8n8.x2.shared.b16 [%0], {%1,%2};" ::"r"(a), "r"(r0), "r"(r1) : "memory");
}
__device__ __forceinline__ void stmat_x4_t(uint32_t a, uint32_t r0, uint32_t r1, uint32_t r2, uint32_t r3) {
    asm volatile("stmatrix.sync.aligned.m8n8.x4.trans.shared.b16 [%0], {%1,%2,%3,%4};" ::"r"(a), "r"(r0), "r"(r1), "r"(r2), "r"(r3) : "memory");
}
struct GeluC { float c0, c1, hr; };
__device__ __forceinline__ GeluC gelu_consts(float r) {
    GeluC c; c.c0 = 0.797884560803f * r; c.c1 = 0.035677408136f * r * r * r; c.hr = 0.5f * r; return c;
}
__device__ __forceinline__ float gelu_s(float a, const GeluC& c) {
    const float p = fmaf(a * a, c.c1, c.c0);
    float th; asm("tanh.approx.f32 %0, %1;" : "=f"(th) : "f"(a * p));
    const float h = a * c.hr;
    return fmaf(h, th, h);
}
__device__ __forceinline__ float ex2(float x) { float r; asm("ex2.approx.ftz.f32 %0, %1;" : "=f"(r) : "f"(x)); return r; }

#define PUBLISH(p, v) st_relaxed(p, v)

template <int TB, uint32_t AHI, uint32_t BHI>
__device__ __forceinline__ void wgmma_n64(float (&d)[32], uint32_t alo, uint32_t blo, bool acc) {
    if (acc) {
        asm volatile("{\n.reg .b64 da, db;\nmov.b64 da, {%32, %35};\nmov.b64 db, {%33, %36};\n"
            "wgmma.mma_async.sync.aligned.m64n64k16.f32.bf16.bf16 {%0, %1, %2, %3, %4, %5, %6, %7, %8, %9, %10, %11, %12, %13, %14, %15, %16, %17, %18, %19, %20, %21, %22, %23, %24, %25, %26, %27, %28, %29, %30, %31}, da, db, 1, 1, 1, 0, %34;\n}\n"
            : "+f"(d[0]), "+f"(d[1]), "+f"(d[2]), "+f"(d[3]), "+f"(d[4]), "+f"(d[5]), "+f"(d[6]), "+f"(d[7]), "+f"(d[8]), "+f"(d[9]), "+f"(d[10]), "+f"(d[11]), "+f"(d[12]), "+f"(d[13]), "+f"(d[14]), "+f"(d[15]), "+f"(d[16]), "+f"(d[17]), "+f"(d[18]), "+f"(d[19]), "+f"(d[20]), "+f"(d[21]), "+f"(d[22]), "+f"(d[23]), "+f"(d[24]), "+f"(d[25]), "+f"(d[26]), "+f"(d[27]), "+f"(d[28]), "+f"(d[29]), "+f"(d[30]), "+f"(d[31])
            : "r"(alo), "r"(blo), "n"(TB), "n"(AHI), "n"(BHI));
    } else {
        asm volatile("{\n.reg .b64 da, db;\nmov.b64 da, {%32, %35};\nmov.b64 db, {%33, %36};\n"
            "wgmma.mma_async.sync.aligned.m64n64k16.f32.bf16.bf16 {%0, %1, %2, %3, %4, %5, %6, %7, %8, %9, %10, %11, %12, %13, %14, %15, %16, %17, %18, %19, %20, %21, %22, %23, %24, %25, %26, %27, %28, %29, %30, %31}, da, db, 0, 1, 1, 0, %34;\n}\n"
            : "=f"(d[0]), "=f"(d[1]), "=f"(d[2]), "=f"(d[3]), "=f"(d[4]), "=f"(d[5]), "=f"(d[6]), "=f"(d[7]), "=f"(d[8]), "=f"(d[9]), "=f"(d[10]), "=f"(d[11]), "=f"(d[12]), "=f"(d[13]), "=f"(d[14]), "=f"(d[15]), "=f"(d[16]), "=f"(d[17]), "=f"(d[18]), "=f"(d[19]), "=f"(d[20]), "=f"(d[21]), "=f"(d[22]), "=f"(d[23]), "=f"(d[24]), "=f"(d[25]), "=f"(d[26]), "=f"(d[27]), "=f"(d[28]), "=f"(d[29]), "=f"(d[30]), "=f"(d[31])
            : "r"(alo), "r"(blo), "n"(TB), "n"(AHI), "n"(BHI));
    }
}
template <int TB, uint32_t AHI, uint32_t BHI>
__device__ __forceinline__ void wgmma_n72(float (&d)[36], uint32_t alo, uint32_t blo, bool acc) {
    if (acc) {
        asm volatile("{\n.reg .b64 da, db;\nmov.b64 da, {%36, %39};\nmov.b64 db, {%37, %40};\n"
            "wgmma.mma_async.sync.aligned.m64n72k16.f32.bf16.bf16 {%0, %1, %2, %3, %4, %5, %6, %7, %8, %9, %10, %11, %12, %13, %14, %15, %16, %17, %18, %19, %20, %21, %22, %23, %24, %25, %26, %27, %28, %29, %30, %31, %32, %33, %34, %35}, da, db, 1, 1, 1, 0, %38;\n}\n"
            : "+f"(d[0]), "+f"(d[1]), "+f"(d[2]), "+f"(d[3]), "+f"(d[4]), "+f"(d[5]), "+f"(d[6]), "+f"(d[7]), "+f"(d[8]), "+f"(d[9]), "+f"(d[10]), "+f"(d[11]), "+f"(d[12]), "+f"(d[13]), "+f"(d[14]), "+f"(d[15]), "+f"(d[16]), "+f"(d[17]), "+f"(d[18]), "+f"(d[19]), "+f"(d[20]), "+f"(d[21]), "+f"(d[22]), "+f"(d[23]), "+f"(d[24]), "+f"(d[25]), "+f"(d[26]), "+f"(d[27]), "+f"(d[28]), "+f"(d[29]), "+f"(d[30]), "+f"(d[31]), "+f"(d[32]), "+f"(d[33]), "+f"(d[34]), "+f"(d[35])
            : "r"(alo), "r"(blo), "n"(TB), "n"(AHI), "n"(BHI));
    } else {
        asm volatile("{\n.reg .b64 da, db;\nmov.b64 da, {%36, %39};\nmov.b64 db, {%37, %40};\n"
            "wgmma.mma_async.sync.aligned.m64n72k16.f32.bf16.bf16 {%0, %1, %2, %3, %4, %5, %6, %7, %8, %9, %10, %11, %12, %13, %14, %15, %16, %17, %18, %19, %20, %21, %22, %23, %24, %25, %26, %27, %28, %29, %30, %31, %32, %33, %34, %35}, da, db, 0, 1, 1, 0, %38;\n}\n"
            : "=f"(d[0]), "=f"(d[1]), "=f"(d[2]), "=f"(d[3]), "=f"(d[4]), "=f"(d[5]), "=f"(d[6]), "=f"(d[7]), "=f"(d[8]), "=f"(d[9]), "=f"(d[10]), "=f"(d[11]), "=f"(d[12]), "=f"(d[13]), "=f"(d[14]), "=f"(d[15]), "=f"(d[16]), "=f"(d[17]), "=f"(d[18]), "=f"(d[19]), "=f"(d[20]), "=f"(d[21]), "=f"(d[22]), "=f"(d[23]), "=f"(d[24]), "=f"(d[25]), "=f"(d[26]), "=f"(d[27]), "=f"(d[28]), "=f"(d[29]), "=f"(d[30]), "=f"(d[31]), "=f"(d[32]), "=f"(d[33]), "=f"(d[34]), "=f"(d[35])
            : "r"(alo), "r"(blo), "n"(TB), "n"(AHI), "n"(BHI));
    }
}
template <int TB, uint32_t AHI, uint32_t BHI>
__device__ __forceinline__ void wgmma_n112(float (&d)[56], uint32_t alo, uint32_t blo, bool acc) {
    if (acc) {
        asm volatile("{\n.reg .b64 da, db;\nmov.b64 da, {%56, %59};\nmov.b64 db, {%57, %60};\n"
            "wgmma.mma_async.sync.aligned.m64n112k16.f32.bf16.bf16 {%0, %1, %2, %3, %4, %5, %6, %7, %8, %9, %10, %11, %12, %13, %14, %15, %16, %17, %18, %19, %20, %21, %22, %23, %24, %25, %26, %27, %28, %29, %30, %31, %32, %33, %34, %35, %36, %37, %38, %39, %40, %41, %42, %43, %44, %45, %46, %47, %48, %49, %50, %51, %52, %53, %54, %55}, da, db, 1, 1, 1, 0, %58;\n}\n"
            : "+f"(d[0]), "+f"(d[1]), "+f"(d[2]), "+f"(d[3]), "+f"(d[4]), "+f"(d[5]), "+f"(d[6]), "+f"(d[7]), "+f"(d[8]), "+f"(d[9]), "+f"(d[10]), "+f"(d[11]), "+f"(d[12]), "+f"(d[13]), "+f"(d[14]), "+f"(d[15]), "+f"(d[16]), "+f"(d[17]), "+f"(d[18]), "+f"(d[19]), "+f"(d[20]), "+f"(d[21]), "+f"(d[22]), "+f"(d[23]), "+f"(d[24]), "+f"(d[25]), "+f"(d[26]), "+f"(d[27]), "+f"(d[28]), "+f"(d[29]), "+f"(d[30]), "+f"(d[31]), "+f"(d[32]), "+f"(d[33]), "+f"(d[34]), "+f"(d[35]), "+f"(d[36]), "+f"(d[37]), "+f"(d[38]), "+f"(d[39]), "+f"(d[40]), "+f"(d[41]), "+f"(d[42]), "+f"(d[43]), "+f"(d[44]), "+f"(d[45]), "+f"(d[46]), "+f"(d[47]), "+f"(d[48]), "+f"(d[49]), "+f"(d[50]), "+f"(d[51]), "+f"(d[52]), "+f"(d[53]), "+f"(d[54]), "+f"(d[55])
            : "r"(alo), "r"(blo), "n"(TB), "n"(AHI), "n"(BHI));
    } else {
        asm volatile("{\n.reg .b64 da, db;\nmov.b64 da, {%56, %59};\nmov.b64 db, {%57, %60};\n"
            "wgmma.mma_async.sync.aligned.m64n112k16.f32.bf16.bf16 {%0, %1, %2, %3, %4, %5, %6, %7, %8, %9, %10, %11, %12, %13, %14, %15, %16, %17, %18, %19, %20, %21, %22, %23, %24, %25, %26, %27, %28, %29, %30, %31, %32, %33, %34, %35, %36, %37, %38, %39, %40, %41, %42, %43, %44, %45, %46, %47, %48, %49, %50, %51, %52, %53, %54, %55}, da, db, 0, 1, 1, 0, %58;\n}\n"
            : "=f"(d[0]), "=f"(d[1]), "=f"(d[2]), "=f"(d[3]), "=f"(d[4]), "=f"(d[5]), "=f"(d[6]), "=f"(d[7]), "=f"(d[8]), "=f"(d[9]), "=f"(d[10]), "=f"(d[11]), "=f"(d[12]), "=f"(d[13]), "=f"(d[14]), "=f"(d[15]), "=f"(d[16]), "=f"(d[17]), "=f"(d[18]), "=f"(d[19]), "=f"(d[20]), "=f"(d[21]), "=f"(d[22]), "=f"(d[23]), "=f"(d[24]), "=f"(d[25]), "=f"(d[26]), "=f"(d[27]), "=f"(d[28]), "=f"(d[29]), "=f"(d[30]), "=f"(d[31]), "=f"(d[32]), "=f"(d[33]), "=f"(d[34]), "=f"(d[35]), "=f"(d[36]), "=f"(d[37]), "=f"(d[38]), "=f"(d[39]), "=f"(d[40]), "=f"(d[41]), "=f"(d[42]), "=f"(d[43]), "=f"(d[44]), "=f"(d[45]), "=f"(d[46]), "=f"(d[47]), "=f"(d[48]), "=f"(d[49]), "=f"(d[50]), "=f"(d[51]), "=f"(d[52]), "=f"(d[53]), "=f"(d[54]), "=f"(d[55])
            : "r"(alo), "r"(blo), "n"(TB), "n"(AHI), "n"(BHI));
    }
}
template <int TB, uint32_t AHI, uint32_t BHI>
__device__ __forceinline__ void wgmma_n112_p(float (&d)[56], uint32_t alo, uint32_t blo, int acc) {
    asm volatile("{\n.reg .b64 da, db;\n.reg .pred p;\nsetp.ne.b32 p, %61, 0;\nmov.b64 da, {%56, %59};\nmov.b64 db, {%57, %60};\n"
        "wgmma.mma_async.sync.aligned.m64n112k16.f32.bf16.bf16 {%0, %1, %2, %3, %4, %5, %6, %7, %8, %9, %10, %11, %12, %13, %14, %15, %16, %17, %18, %19, %20, %21, %22, %23, %24, %25, %26, %27, %28, %29, %30, %31, %32, %33, %34, %35, %36, %37, %38, %39, %40, %41, %42, %43, %44, %45, %46, %47, %48, %49, %50, %51, %52, %53, %54, %55}, da, db, p, 1, 1, 0, %58;\n}\n"
        : "+f"(d[0]), "+f"(d[1]), "+f"(d[2]), "+f"(d[3]), "+f"(d[4]), "+f"(d[5]), "+f"(d[6]), "+f"(d[7]), "+f"(d[8]), "+f"(d[9]), "+f"(d[10]), "+f"(d[11]), "+f"(d[12]), "+f"(d[13]), "+f"(d[14]), "+f"(d[15]), "+f"(d[16]), "+f"(d[17]), "+f"(d[18]), "+f"(d[19]), "+f"(d[20]), "+f"(d[21]), "+f"(d[22]), "+f"(d[23]), "+f"(d[24]), "+f"(d[25]), "+f"(d[26]), "+f"(d[27]), "+f"(d[28]), "+f"(d[29]), "+f"(d[30]), "+f"(d[31]), "+f"(d[32]), "+f"(d[33]), "+f"(d[34]), "+f"(d[35]), "+f"(d[36]), "+f"(d[37]), "+f"(d[38]), "+f"(d[39]), "+f"(d[40]), "+f"(d[41]), "+f"(d[42]), "+f"(d[43]), "+f"(d[44]), "+f"(d[45]), "+f"(d[46]), "+f"(d[47]), "+f"(d[48]), "+f"(d[49]), "+f"(d[50]), "+f"(d[51]), "+f"(d[52]), "+f"(d[53]), "+f"(d[54]), "+f"(d[55])
        : "r"(alo), "r"(blo), "n"(TB), "n"(AHI), "n"(BHI), "r"(acc));
}
template <int TB, uint32_t AHI, uint32_t BHI>
__device__ __forceinline__ void wgmma_n168(float (&d)[84], uint32_t alo, uint32_t blo, bool acc) {
    if (acc) {
        asm volatile("{\n.reg .b64 da, db;\nmov.b64 da, {%84, %87};\nmov.b64 db, {%85, %88};\n"
            "wgmma.mma_async.sync.aligned.m64n168k16.f32.bf16.bf16 {%0, %1, %2, %3, %4, %5, %6, %7, %8, %9, %10, %11, %12, %13, %14, %15, %16, %17, %18, %19, %20, %21, %22, %23, %24, %25, %26, %27, %28, %29, %30, %31, %32, %33, %34, %35, %36, %37, %38, %39, %40, %41, %42, %43, %44, %45, %46, %47, %48, %49, %50, %51, %52, %53, %54, %55, %56, %57, %58, %59, %60, %61, %62, %63, %64, %65, %66, %67, %68, %69, %70, %71, %72, %73, %74, %75, %76, %77, %78, %79, %80, %81, %82, %83}, da, db, 1, 1, 1, 0, %86;\n}\n"
            : "+f"(d[0]), "+f"(d[1]), "+f"(d[2]), "+f"(d[3]), "+f"(d[4]), "+f"(d[5]), "+f"(d[6]), "+f"(d[7]), "+f"(d[8]), "+f"(d[9]), "+f"(d[10]), "+f"(d[11]), "+f"(d[12]), "+f"(d[13]), "+f"(d[14]), "+f"(d[15]), "+f"(d[16]), "+f"(d[17]), "+f"(d[18]), "+f"(d[19]), "+f"(d[20]), "+f"(d[21]), "+f"(d[22]), "+f"(d[23]), "+f"(d[24]), "+f"(d[25]), "+f"(d[26]), "+f"(d[27]), "+f"(d[28]), "+f"(d[29]), "+f"(d[30]), "+f"(d[31]), "+f"(d[32]), "+f"(d[33]), "+f"(d[34]), "+f"(d[35]), "+f"(d[36]), "+f"(d[37]), "+f"(d[38]), "+f"(d[39]), "+f"(d[40]), "+f"(d[41]), "+f"(d[42]), "+f"(d[43]), "+f"(d[44]), "+f"(d[45]), "+f"(d[46]), "+f"(d[47]), "+f"(d[48]), "+f"(d[49]), "+f"(d[50]), "+f"(d[51]), "+f"(d[52]), "+f"(d[53]), "+f"(d[54]), "+f"(d[55]), "+f"(d[56]), "+f"(d[57]), "+f"(d[58]), "+f"(d[59]), "+f"(d[60]), "+f"(d[61]), "+f"(d[62]), "+f"(d[63]), "+f"(d[64]), "+f"(d[65]), "+f"(d[66]), "+f"(d[67]), "+f"(d[68]), "+f"(d[69]), "+f"(d[70]), "+f"(d[71]), "+f"(d[72]), "+f"(d[73]), "+f"(d[74]), "+f"(d[75]), "+f"(d[76]), "+f"(d[77]), "+f"(d[78]), "+f"(d[79]), "+f"(d[80]), "+f"(d[81]), "+f"(d[82]), "+f"(d[83])
            : "r"(alo), "r"(blo), "n"(TB), "n"(AHI), "n"(BHI));
    } else {
        asm volatile("{\n.reg .b64 da, db;\nmov.b64 da, {%84, %87};\nmov.b64 db, {%85, %88};\n"
            "wgmma.mma_async.sync.aligned.m64n168k16.f32.bf16.bf16 {%0, %1, %2, %3, %4, %5, %6, %7, %8, %9, %10, %11, %12, %13, %14, %15, %16, %17, %18, %19, %20, %21, %22, %23, %24, %25, %26, %27, %28, %29, %30, %31, %32, %33, %34, %35, %36, %37, %38, %39, %40, %41, %42, %43, %44, %45, %46, %47, %48, %49, %50, %51, %52, %53, %54, %55, %56, %57, %58, %59, %60, %61, %62, %63, %64, %65, %66, %67, %68, %69, %70, %71, %72, %73, %74, %75, %76, %77, %78, %79, %80, %81, %82, %83}, da, db, 0, 1, 1, 0, %86;\n}\n"
            : "=f"(d[0]), "=f"(d[1]), "=f"(d[2]), "=f"(d[3]), "=f"(d[4]), "=f"(d[5]), "=f"(d[6]), "=f"(d[7]), "=f"(d[8]), "=f"(d[9]), "=f"(d[10]), "=f"(d[11]), "=f"(d[12]), "=f"(d[13]), "=f"(d[14]), "=f"(d[15]), "=f"(d[16]), "=f"(d[17]), "=f"(d[18]), "=f"(d[19]), "=f"(d[20]), "=f"(d[21]), "=f"(d[22]), "=f"(d[23]), "=f"(d[24]), "=f"(d[25]), "=f"(d[26]), "=f"(d[27]), "=f"(d[28]), "=f"(d[29]), "=f"(d[30]), "=f"(d[31]), "=f"(d[32]), "=f"(d[33]), "=f"(d[34]), "=f"(d[35]), "=f"(d[36]), "=f"(d[37]), "=f"(d[38]), "=f"(d[39]), "=f"(d[40]), "=f"(d[41]), "=f"(d[42]), "=f"(d[43]), "=f"(d[44]), "=f"(d[45]), "=f"(d[46]), "=f"(d[47]), "=f"(d[48]), "=f"(d[49]), "=f"(d[50]), "=f"(d[51]), "=f"(d[52]), "=f"(d[53]), "=f"(d[54]), "=f"(d[55]), "=f"(d[56]), "=f"(d[57]), "=f"(d[58]), "=f"(d[59]), "=f"(d[60]), "=f"(d[61]), "=f"(d[62]), "=f"(d[63]), "=f"(d[64]), "=f"(d[65]), "=f"(d[66]), "=f"(d[67]), "=f"(d[68]), "=f"(d[69]), "=f"(d[70]), "=f"(d[71]), "=f"(d[72]), "=f"(d[73]), "=f"(d[74]), "=f"(d[75]), "=f"(d[76]), "=f"(d[77]), "=f"(d[78]), "=f"(d[79]), "=f"(d[80]), "=f"(d[81]), "=f"(d[82]), "=f"(d[83])
            : "r"(alo), "r"(blo), "n"(TB), "n"(AHI), "n"(BHI));
    }
}
template <int TB, uint32_t BHI>
__device__ __forceinline__ void wgmma_rs_n32(float (&d)[16], uint32_t a0, uint32_t a1, uint32_t a2, uint32_t a3, uint32_t blo, bool acc) {
    if (acc) {
        asm volatile("{\n.reg .b64 db;\nmov.b64 db, {%20, %22};\n"
            "wgmma.mma_async.sync.aligned.m64n32k16.f32.bf16.bf16 {%0, %1, %2, %3, %4, %5, %6, %7, %8, %9, %10, %11, %12, %13, %14, %15}, {%16, %17, %18, %19}, db, 1, 1, 1, %21;\n}\n"
            : "+f"(d[0]), "+f"(d[1]), "+f"(d[2]), "+f"(d[3]), "+f"(d[4]), "+f"(d[5]), "+f"(d[6]), "+f"(d[7]), "+f"(d[8]), "+f"(d[9]), "+f"(d[10]), "+f"(d[11]), "+f"(d[12]), "+f"(d[13]), "+f"(d[14]), "+f"(d[15])
            : "r"(a0), "r"(a1), "r"(a2), "r"(a3), "r"(blo), "n"(TB), "n"(BHI));
    } else {
        asm volatile("{\n.reg .b64 db;\nmov.b64 db, {%20, %22};\n"
            "wgmma.mma_async.sync.aligned.m64n32k16.f32.bf16.bf16 {%0, %1, %2, %3, %4, %5, %6, %7, %8, %9, %10, %11, %12, %13, %14, %15}, {%16, %17, %18, %19}, db, 0, 1, 1, %21;\n}\n"
            : "=f"(d[0]), "=f"(d[1]), "=f"(d[2]), "=f"(d[3]), "=f"(d[4]), "=f"(d[5]), "=f"(d[6]), "=f"(d[7]), "=f"(d[8]), "=f"(d[9]), "=f"(d[10]), "=f"(d[11]), "=f"(d[12]), "=f"(d[13]), "=f"(d[14]), "=f"(d[15])
            : "r"(a0), "r"(a1), "r"(a2), "r"(a3), "r"(blo), "n"(TB), "n"(BHI));
    }
}
template <int TB, uint32_t BHI>
__device__ __forceinline__ void wgmma_rs_n112(float (&d)[56], uint32_t a0, uint32_t a1, uint32_t a2, uint32_t a3, uint32_t blo, bool acc) {
    if (acc) {
        asm volatile("{\n.reg .b64 db;\nmov.b64 db, {%60, %62};\n"
            "wgmma.mma_async.sync.aligned.m64n112k16.f32.bf16.bf16 {%0, %1, %2, %3, %4, %5, %6, %7, %8, %9, %10, %11, %12, %13, %14, %15, %16, %17, %18, %19, %20, %21, %22, %23, %24, %25, %26, %27, %28, %29, %30, %31, %32, %33, %34, %35, %36, %37, %38, %39, %40, %41, %42, %43, %44, %45, %46, %47, %48, %49, %50, %51, %52, %53, %54, %55}, {%56, %57, %58, %59}, db, 1, 1, 1, %61;\n}\n"
            : "+f"(d[0]), "+f"(d[1]), "+f"(d[2]), "+f"(d[3]), "+f"(d[4]), "+f"(d[5]), "+f"(d[6]), "+f"(d[7]), "+f"(d[8]), "+f"(d[9]), "+f"(d[10]), "+f"(d[11]), "+f"(d[12]), "+f"(d[13]), "+f"(d[14]), "+f"(d[15]), "+f"(d[16]), "+f"(d[17]), "+f"(d[18]), "+f"(d[19]), "+f"(d[20]), "+f"(d[21]), "+f"(d[22]), "+f"(d[23]), "+f"(d[24]), "+f"(d[25]), "+f"(d[26]), "+f"(d[27]), "+f"(d[28]), "+f"(d[29]), "+f"(d[30]), "+f"(d[31]), "+f"(d[32]), "+f"(d[33]), "+f"(d[34]), "+f"(d[35]), "+f"(d[36]), "+f"(d[37]), "+f"(d[38]), "+f"(d[39]), "+f"(d[40]), "+f"(d[41]), "+f"(d[42]), "+f"(d[43]), "+f"(d[44]), "+f"(d[45]), "+f"(d[46]), "+f"(d[47]), "+f"(d[48]), "+f"(d[49]), "+f"(d[50]), "+f"(d[51]), "+f"(d[52]), "+f"(d[53]), "+f"(d[54]), "+f"(d[55])
            : "r"(a0), "r"(a1), "r"(a2), "r"(a3), "r"(blo), "n"(TB), "n"(BHI));
    } else {
        asm volatile("{\n.reg .b64 db;\nmov.b64 db, {%60, %62};\n"
            "wgmma.mma_async.sync.aligned.m64n112k16.f32.bf16.bf16 {%0, %1, %2, %3, %4, %5, %6, %7, %8, %9, %10, %11, %12, %13, %14, %15, %16, %17, %18, %19, %20, %21, %22, %23, %24, %25, %26, %27, %28, %29, %30, %31, %32, %33, %34, %35, %36, %37, %38, %39, %40, %41, %42, %43, %44, %45, %46, %47, %48, %49, %50, %51, %52, %53, %54, %55}, {%56, %57, %58, %59}, db, 0, 1, 1, %61;\n}\n"
            : "=f"(d[0]), "=f"(d[1]), "=f"(d[2]), "=f"(d[3]), "=f"(d[4]), "=f"(d[5]), "=f"(d[6]), "=f"(d[7]), "=f"(d[8]), "=f"(d[9]), "=f"(d[10]), "=f"(d[11]), "=f"(d[12]), "=f"(d[13]), "=f"(d[14]), "=f"(d[15]), "=f"(d[16]), "=f"(d[17]), "=f"(d[18]), "=f"(d[19]), "=f"(d[20]), "=f"(d[21]), "=f"(d[22]), "=f"(d[23]), "=f"(d[24]), "=f"(d[25]), "=f"(d[26]), "=f"(d[27]), "=f"(d[28]), "=f"(d[29]), "=f"(d[30]), "=f"(d[31]), "=f"(d[32]), "=f"(d[33]), "=f"(d[34]), "=f"(d[35]), "=f"(d[36]), "=f"(d[37]), "=f"(d[38]), "=f"(d[39]), "=f"(d[40]), "=f"(d[41]), "=f"(d[42]), "=f"(d[43]), "=f"(d[44]), "=f"(d[45]), "=f"(d[46]), "=f"(d[47]), "=f"(d[48]), "=f"(d[49]), "=f"(d[50]), "=f"(d[51]), "=f"(d[52]), "=f"(d[53]), "=f"(d[54]), "=f"(d[55])
            : "r"(a0), "r"(a1), "r"(a2), "r"(a3), "r"(blo), "n"(TB), "n"(BHI));
    }
}

struct Params {
    CUtensorMap tm_x;
    CUtensorMap tm_win;
    CUtensorMap tm_wsp;
    CUtensorMap tm_wqkv;
    CUtensorMap tm_wo;
    CUtensorMap tm_wout;
    const bf16* x;
    const bf16* wqkv;
    const bf16* wo;
    const bf16* win;
    const bf16* wsp;
    const bf16* bsp;
    const bf16* wout;
    bf16* out;
};

__device__ __forceinline__ float quad_sum(float v) {
    v += __shfl_xor_sync(0xffffffffu, v, 1);
    v += __shfl_xor_sync(0xffffffffu, v, 2);
    return v;
}

__device__ __forceinline__ void quad_transpose(uint32_t& v0, uint32_t& v1, uint32_t& v2, uint32_t& v3, int t) {
    const bool o1 = t & 1, o2 = t & 2;
    uint32_t x0 = __shfl_xor_sync(0xffffffffu, o1 ? v0 : v1, 1), x1 = __shfl_xor_sync(0xffffffffu, o1 ? v2 : v3, 1);
    if (o1) { v0 = x0; v2 = x1; } else { v1 = x0; v3 = x1; }
    x0 = __shfl_xor_sync(0xffffffffu, o2 ? v0 : v2, 2); x1 = __shfl_xor_sync(0xffffffffu, o2 ? v1 : v3, 2);
    if (o2) { v0 = x0; v1 = x1; } else { v2 = x0; v3 = x1; }
}

__global__ void __cluster_dims__(2, 1, 1) __launch_bounds__(384, 1)
fused_kernel(const __grid_constant__ Params P) {
    extern __shared__ __align__(1024) uint8_t smem_raw[];
    const uint32_t sb = (smem_u32(smem_raw) + 1023u) & ~1023u;
    const uint32_t bars = sb + BAR_OFF;
    const int h = blockIdx.x & 1;
    const int pr = blockIdx.x >> 1;
    const int i = pr & 15, jj = pr >> 4, j = 2 * jj + h;
    int lane = threadIdx.x & 31, g = lane >> 2, t = lane & 3;
#define RELANE() do { asm volatile("mov.u32 %0, %%laneid;" : "=r"(lane)); g = lane >> 2; t = lane & 3; } while (0)
    const int warp = __shfl_sync(0xffffffffu, threadIdx.x >> 5, 0);
    if (lane == 0) {
        if (warp == 8) {
            mbar_init(bars + 8 * B_FULLX, 1);
            mbar_init(bars + 8 * (B_FULLX + 1), 1);
            mbar_expect_tx(bars + 8 * B_FULLX, 4 * GRAN);
            mbar_expect_tx(bars + 8 * (B_FULLX + 1), 4 * GRAN);
#pragma unroll 1
            for (int r = 0; r < 14; r++) {
                const int hf = r >= 7, kb = r - 7 * hf;
                tma_2d(sb + XN_OFF + kb * 16384 + hf * 8192, &P.tm_x, kb * 64, i * 128 + hf * 64, bars + 8 * (B_FULLX + hf));
            }
        } else if (warp < 8) {
            mbar_init(bars + 8 * (B_FULL + warp), 1);
            mbar_init(bars + 8 * (B_FULL + 8 + warp), 1);
            mbar_init(bars + 8 * (B_DONE + warp), 4);
            mbar_init(bars + 8 * (B_DONE + 8 + warp), 4);
        } else {
            mbar_init(bars + 8 * (B_Z2SFREE + warp - 9), 2);
            if (warp == 9) {
                sts_u32(sb + UFLAG_OFF, 0u);
                sts_v4(sb + SEL_OFF, make_uint4(0u, 0x11u, 0x22u, 0x33u));
                sts_v4(sb + SEL_OFF + 16, make_uint4(0x44u, 0u, 0u, 0u));
                sts_v4(sb + SEL_OFF + 32, make_uint4(0u, 0u, 0u, 0u));
                sts_u32(sb + SEL_OFF + 48, 12u);
                asm volatile("prefetch.tensormap [%0];" ::"l"(&P.tm_win) : "memory");
                asm volatile("prefetch.tensormap [%0];" ::"l"(&P.tm_wqkv) : "memory");
            }
            mbar_init(bars + 8 * (B_OREADY + warp - 9), 1);
            if (warp > 9) mbar_init(bars + 8 * (B_STATS + warp - 10), 1);
        }
        asm volatile("fence.mbarrier_init.release.cluster;" ::: "memory");
    }
    __syncwarp();
    cluster_arrive_relaxed();

    if (warp < 8) {
        const int wg = warp >> 2, w = warp & 3;
        const bool sig2 = (lane == 0) && (w < 2);
        uint32_t rdone;
        asm volatile("mapa.shared::cluster.u32 %0, %1, %2;" : "=r"(rdone) : "r"(bars + 8 * B_DONE), "r"(h ^ (w & 1)));
#define SIGNAL_LOCAL(step) do { if (sig2) mbar_arrive(bars + 8 * (B_DONE + ((step) & 15))); } while (0)
#define SIGNAL_DONE(step) do { if (sig2) mbar_arrive_cl(rdone + 8 * ((step) & 15)); } while (0)
        uint32_t xr[16];
        asm volatile("setmaxnreg.inc.sync.aligned.u32 216;");
        bar_sync(9, 384);
        if (threadIdx.x == 0) TS(53);
        const uint32_t dA_xn = dlo(sb + XN_OFF + wg * 8192, 16);
        const uint32_t dB_ra = dlo(sb + RINGA_OFF, 8192);
        float acc_a[56], acc_b[56], acc_c[84];
        float rs0, rs1;
        unsigned epoch;
        {
            uint32_t xf[28][4];
            const uint32_t la = sb + XN_OFF + (warp * 16 + (lane & 15)) * 128 + (((lane >> 4) ^ (lane & 7)) << 4);
            mbar_wait(bars + 8 * (B_FULLX + wg), 0);
            if (threadIdx.x == 0) TS(56);
            if (threadIdx.x == 128) TS(15);
#pragma unroll
            for (int c = 0; c < 28; c++) ldmat_x4(xf[c][0], xf[c][1], xf[c][2], xf[c][3], (la ^ ((c & 3) << 5)) + (c >> 2) * 16384);
#pragma unroll
            for (int q = 0; q < 4; q++) ldmat_x4(xr[4 * q], xr[4 * q + 1], xr[4 * q + 2], xr[4 * q + 3], (la ^ (q << 5)) + min(j, 6) * 16384);
            float sA[4] = {0.f, 0.f, 0.f, 0.f}, sB[4] = {0.f, 0.f, 0.f, 0.f}, sC[4] = {0.f, 0.f, 0.f, 0.f}, sD[4] = {0.f, 0.f, 0.f, 0.f};
            const uint32_t ONES = 0x3F803F80u;
#pragma unroll
            for (int c = 0; c < 28; c += 4) {
                mma16816(sA, xf[c][0], xf[c][1], xf[c][2], xf[c][3], ONES, ONES);
                mma16816(sB, xf[c + 1][0], xf[c + 1][1], xf[c + 1][2], xf[c + 1][3], ONES, ONES);
                mma16816(sC, xf[c + 2][0], xf[c + 2][1], xf[c + 2][2], xf[c + 2][3], ONES, ONES);
                mma16816(sD, xf[c + 3][0], xf[c + 3][1], xf[c + 3][2], xf[c + 3][3], ONES, ONES);
            }
            const float ma = ((sA[0] + sB[0]) + (sC[0] + sD[0])) * (1.0f / 448.0f), mb = ((sA[2] + sB[2]) + (sC[2] + sD[2])) * (1.0f / 448.0f);
            const uint32_t ma2 = pack_bf16(ma, ma), mb2 = pack_bf16(mb, mb);
            const float dma = ma - bf_lo(ma2), dmb = mb - bf_lo(mb2);
            if (threadIdx.x == 0) TS(57);
            if (threadIdx.x == 128) TS(12);
#define CENTRE(kb_) do { \
                _Pragma("unroll") \
                for (int c = 4 * (kb_); c < 4 * (kb_) + 4; c++) { \
                    xf[c][0] = sub_bf16x2(xf[c][0], ma2); xf[c][1] = sub_bf16x2(xf[c][1], mb2); \
                    xf[c][2] = sub_bf16x2(xf[c][2], ma2); xf[c][3] = sub_bf16x2(xf[c][3], mb2); \
                    asm volatile("" : "+r"(xf[c][0]), "+r"(xf[c][1]), "+r"(xf[c][2]), "+r"(xf[c][3])); \
                } \
            } while (0)
#define XSTORE(kb_) do { \
                _Pragma("unroll") \
                for (int c = 4 * (kb_); c < 4 * (kb_) + 4; c++) stmat_x4((la ^ ((c & 3) << 5)) + (c >> 2) * 16384, xf[c][0], xf[c][1], xf[c][2], xf[c][3]); \
            } while (0)
            CENTRE(0);
            float qa = 0.f, qb = 0.f, qa2 = 0.f, qb2 = 0.f;
            constexpr uint64_t VSCHED = 0x1C16100C08040000ull;
#pragma unroll
            for (int kb = 0; kb < 7; kb++) {
                wait_full(bars, kb);
                TS2(threadIdx.x == 0, kb);
                wgmma_fence();
#pragma unroll
                for (int k = 0; k < 4; k++)
                    wgmma_rs_n112<1, HI_SW128>(acc_a, xf[4 * kb + k][0], xf[4 * kb + k][1], xf[4 * kb + k][2], xf[4 * kb + k][3],
                                               dB_ra + wslot(kb) * 1024 + k * 128, (kb | k) != 0);
                wgmma_commit();
                if (kb < 6) CENTRE(kb + 1);
                if (kb > 0) { wgmma_wait<1>(); SIGNAL_LOCAL(kb - 1); }
                if (kb == 1) {
                    epoch = ld_relaxed(&g_done);
                    RELANE();
                    if (t == 0) st_relaxed_v4(g_stats + ((i * 8 + j) * 64 + warp * 8 + g), make_uint4(0u, 0u, 0u, 0u));
                    XSTORE(0);
                }
                if (kb == 2) { XSTORE(1); cluster_wait(); }
                if (kb == 3) { XSTORE(2); XSTORE(3); }
                if (kb == 4) { XSTORE(4); XSTORE(5); }
                if (kb == 5) { XSTORE(6); fence_async_smem(); }
                if (kb == 6) { bar_sync(LN_BAR); if (threadIdx.x == 0) TS(0); if (threadIdx.x == 128) TS(58); }
#pragma unroll
                for (int c = 0; c < 28; c += 2) {
                    if (c < (int)((VSCHED >> (8 * kb)) & 255u) || c >= (int)((VSCHED >> (8 * kb + 8)) & 255u)) continue;
                    const uint32_t pa = fma_bf16x2(xf[c + 1][2], xf[c + 1][2], fma_bf16x2(xf[c + 1][0], xf[c + 1][0], fma_bf16x2(xf[c][2], xf[c][2], mul_bf16x2(xf[c][0], xf[c][0]))));
                    const uint32_t pb = fma_bf16x2(xf[c + 1][3], xf[c + 1][3], fma_bf16x2(xf[c + 1][1], xf[c + 1][1], fma_bf16x2(xf[c][3], xf[c][3], mul_bf16x2(xf[c][1], xf[c][1]))));
                    qa += bf_lo(pa); qa2 += bf_hi(pa); qb += bf_lo(pb); qb2 += bf_hi(pb);
                }
                asm volatile("" : "+f"(qa), "+f"(qb), "+f"(qa2), "+f"(qb2));
            }
            rs0 = rsqrtf(fmaxf(quad_sum(qa + qa2) * (1.0f / 448.0f) - dma * dma, 0.f) + 1e-5f);
            rs1 = rsqrtf(fmaxf(quad_sum(qb + qb2) * (1.0f / 448.0f) - dmb * dmb, 0.f) + 1e-5f);
        }
        const GeluC G0 = gelu_consts(rs0), G1 = gelu_consts(rs1);
        epoch = (epoch >> 7) + 1u;
        const uint32_t tag = (epoch % 3u) + 1u;
        uint32_t z2p[28];
        const uint32_t dB_q = dlo(sb + RINGA_OFF, 128);
        {
            float s0 = 0.f, q0 = 0.f, s1 = 0.f, q1 = 0.f;
#pragma unroll
            for (int kb = 0; kb < 7; kb++) {
                wait_full(bars, S_J2 + kb);
                TS2(threadIdx.x == 0, 7 + kb);
                wgmma_fence();
#pragma unroll
                for (int k = 0; k < 4; k++)
                    wgmma_n112<1, HI_SW128, HI_SW128>(acc_b, dA_xn + kb * 1024 + k * 2, dB_ra + wslot(kb + 7) * 1024 + k * 128, (kb | k) != 0);
                wgmma_commit();
                if (kb == 1) { wgmma_wait<2>(); SIGNAL_LOCAL(S_J2 - 1); reg_fence(acc_a); if (threadIdx.x == 0) TS(1); }
                if (kb == 2) { wgmma_wait<1>(); SIGNAL_LOCAL(S_J2); SIGNAL_LOCAL(S_J2 + 1); }
                if (kb >= 3 && kb < 6) { wgmma_wait<1>(); SIGNAL_LOCAL(S_J2 + kb - 1); }
                if (kb == 1 || kb == 2) {
#pragma unroll
                    for (int b = (kb == 1 ? 0 : GSPLIT); b < (kb == 1 ? GSPLIT : 14); b++) {
                        if (b >= 14) continue;
                        const float v0 = gelu_s(acc_a[4 * b], G0), v1 = gelu_s(acc_a[4 * b + 1], G0);
                        const float v2 = gelu_s(acc_a[4 * b + 2], G1), v3 = gelu_s(acc_a[4 * b + 3], G1);
                        s0 += v0 + v1; q0 = fmaf(v0, v0, fmaf(v1, v1, q0));
                        s1 += v2 + v3; q1 = fmaf(v2, v2, fmaf(v3, v3, q1));
                        z2p[2 * b] = pack_bf16(v0, v1); z2p[2 * b + 1] = pack_bf16(v2, v3);
                        asm volatile("" : "+r"(z2p[2 * b]), "+r"(z2p[2 * b + 1]));
                    }
                }
                if (kb == 2) {
                    s0 = quad_sum(s0); q0 = quad_sum(q0); s1 = quad_sum(s1); q1 = quad_sum(q1);
                    RELANE();
                    if (t == 0) {
                        uint4 pk;
                        pk.x = (__float_as_uint(s0) & ~3u) | tag; pk.y = (__float_as_uint(q0) & ~3u) | tag;
                        pk.z = (__float_as_uint(s1) & ~3u) | tag; pk.w = (__float_as_uint(q1) & ~3u) | tag;
                        st_relaxed_v4(g_stats + ((i * 8 + j) * 64 + warp * 8 + g), pk);
                    }
                    if (threadIdx.x == 0) TS(2);
                }
            }
            wgmma_wait<1>();
            SIGNAL_LOCAL(S_J2 + 5);
        }
        uint32_t z1p[28];
        {
#pragma unroll
            for (int kb = 0; kb < 7; kb++) {
                wait_full(bars, S_J3 + kb);
                TS2(threadIdx.x == 0, 14 + kb);
                wgmma_fence();
#pragma unroll
                for (int k = 0; k < 4; k++)
                    wgmma_n168<1, HI_SW128, hi_sbo(256)>(acc_c, dA_xn + kb * 1024 + k * 2, dB_q + (kb & 3) * (WQ_BYTES >> 4) + k * 336, (kb | k) != 0);
                wgmma_commit();
                if (kb == 0) {
                    wgmma_wait<1>();
                    SIGNAL_LOCAL(S_J3 - 1);
                    reg_fence(acc_b);
                    RELANE();
                    if (threadIdx.x == 0) TS(54);
                    mbar_wait(bars + 8 * (B_STATS + wg), 0);
                    wait_done(bars, S_J3 - 1);
                    if (threadIdx.x == 0) TS(3);
                }
                if (kb < 2) {
                    const uint4 st = lds_v4(sb + STAT_OFF + (warp * 8 + g) * 16);
                    const float r0 = __uint_as_float(st.x), n0 = __uint_as_float(st.y), r1 = __uint_as_float(st.z), n1 = __uint_as_float(st.w);
                    const int m = lane >> 3;
                    const uint32_t sa = sb + Z2S_OFF + (warp * 2 + (m & 1)) * 1792 + ((m >> 1) * 8 + (lane & 7)) * 16;
#pragma unroll
                    for (int b = 0; b < 14; b += 2) {
                        if ((kb == 0) != (b < NSPLIT)) continue;
                        asm volatile("" : "+r"(z2p[2 * b]));
                        stmat_x4_t(sa + b * 128,
                                   pack_bf16(fmaf(bf_lo(z2p[2 * b]), r0, n0), fmaf(bf_hi(z2p[2 * b]), r0, n0)),
                                   pack_bf16(fmaf(bf_lo(z2p[2 * b + 1]), r1, n1), fmaf(bf_hi(z2p[2 * b + 1]), r1, n1)),
                                   pack_bf16(fmaf(bf_lo(z2p[2 * b + 2]), r0, n0), fmaf(bf_hi(z2p[2 * b + 2]), r0, n0)),
                                   pack_bf16(fmaf(bf_lo(z2p[2 * b + 3]), r1, n1), fmaf(bf_hi(z2p[2 * b + 3]), r1, n1)));
                    }
                    if (kb == (NSPLIT < 14)) {
                        fence_async_smem();
                        bar_arrive(3 + wg, 160);
                        if (threadIdx.x == 0) TS(4);
                    }
                }
                if (kb > 0) {
                    wgmma_wait<1>();
                    if (kb == 1) SIGNAL_LOCAL(S_J3); else SIGNAL_DONE(S_J3 + kb - 1);
                }
#pragma unroll
                for (int b = 3 * kb - 6; b < 3 * kb - 3; b++) {
                    if (b < 0 || b >= 14) continue;
                    z1p[2 * b] = pack_bf16(gelu_s(acc_b[4 * b], G0), gelu_s(acc_b[4 * b + 1], G0));
                    z1p[2 * b + 1] = pack_bf16(gelu_s(acc_b[4 * b + 2], G1), gelu_s(acc_b[4 * b + 3], G1));
                    asm volatile("" : "+r"(z1p[2 * b]), "+r"(z1p[2 * b + 1]));
                }
            }
        }
        if (threadIdx.x == 0) TS(55);
        RELANE();
        const int row0 = i * 128 + warp * 16 + g;
        const uint32_t dA_g = dlo(sb + wg * 8192, 16);
        const uint32_t dB_g = dlo(sb + 16384, 1792);
        int pos = 1;
        int s = S_G2 + 1;
#define G2_ISSUE() do { \
            wait_full(bars, s); \
            TS3(threadIdx.x == 0, s - S_G2); \
            const uint32_t ro = gstage(pos) >> 4; \
            wgmma_fence(); \
            _Pragma("unroll") \
            for (int k = 0; k < G2K; k++) wgmma_n112<0, HI_SW128, HI_NOSW>(acc_a, dA_g + ro + k * 2, dB_g + ro + k * 224, true); \
        } while (0)
#define G2_RETIRE0() do { \
            wgmma_commit(); \
            wgmma_wait<0>(); \
            SIGNAL_DONE(s); \
            pos = pos == 4 ? 0 : pos + 1; \
            s++; \
        } while (0)
#define G2_RETIRE() do { \
            wgmma_commit(); \
            wgmma_wait<1>(); \
            SIGNAL_DONE(s - 1); \
            pos = pos == 4 ? 0 : pos + 1; \
            s++; \
        } while (0)
        {
            wait_full(bars, S_G2);
            if (threadIdx.x == 0) TS(6);
            wgmma_fence();
#pragma unroll
            for (int k = 0; k < 4; k++) wgmma_n112<0, HI_SW128, HI_NOSW>(acc_a, dA_g + k * 2, dB_g + k * 224, k != 0);
            wgmma_commit();
            wgmma_wait<1>();
            SIGNAL_DONE(S_G2 - 1);
            reg_fence(acc_c);
            if (threadIdx.x == 0) TS(7);
            uint32_t pk[42];
#pragma unroll
            for (int b = 7; b < 21; b++) {
                pk[2 * b] = pack_bf16(acc_c[4 * b] * rs0, acc_c[4 * b + 1] * rs0);
                pk[2 * b + 1] = pack_bf16(acc_c[4 * b + 2] * rs1, acc_c[4 * b + 3] * rs1);
                asm volatile("" : "+r"(pk[2 * b]), "+r"(pk[2 * b + 1]));
            }
            if (warp == 7) {
                uint4* hp = g_halo + (size_t)((i * 8 + j) * 14) * 32 + lane;
#pragma unroll
                for (int c = 0; c < 14; c++) st_relaxed_v4(hp + c * 32, make_uint4(pk[14 + 2 * c], epoch, pk[15 + 2 * c], epoch));
            }
            G2_ISSUE();
            G2_RETIRE();
            wait_done(bars, S_J3 + 6);
            const int m = lane >> 3;
            const int r = warp * 16 + (m & 1) * 8 + (lane & 7);
            const uint32_t sk = sb + KV_OFF + (m >> 1) * K_CH + (r & 1) * K_PAR + (16 + (r >> 1)) * 16;
#pragma unroll
            for (int c = 0; c < 14; c += 2) stmat_x4(sk + c * K_CH, pk[14 + 2 * c], pk[15 + 2 * c], pk[16 + 2 * c], pk[17 + 2 * c]);
            G2_ISSUE();
            G2_RETIRE();
            asm volatile("" : "+f"(rs0), "+f"(rs1));
#pragma unroll
            for (int b = 0; b < 7; b++) {
                pk[2 * b] = pack_bf16(acc_c[4 * b] * rs0, acc_c[4 * b + 1] * rs0);
                pk[2 * b + 1] = pack_bf16(acc_c[4 * b + 2] * rs1, acc_c[4 * b + 3] * rs1);
            }
            const uint32_t sq = sb + QQ_OFF + (m >> 1) * Q_CH + (r & 1) * Q_PAR + (r >> 1) * 16;
            stmat_x4(sq, pk[0], pk[1], pk[2], pk[3]);
            stmat_x4(sq + 2 * Q_CH, pk[4], pk[5], t < 2 ? pk[6] : 0u, t < 2 ? pk[7] : 0u);
            stmat_x4(sq + 4 * Q_CH, t < 2 ? 0u : pk[6], t < 2 ? 0u : pk[7], pk[8], pk[9]);
            stmat_x4(sq + 6 * Q_CH, pk[10], pk[11], pk[12], pk[13]);
        }
        wgmma_wait<0>();
        SIGNAL_DONE(s - 1);
#pragma unroll 1
        while (s < S_G2 + ATT_START - 1) { G2_ISSUE(); G2_RETIRE0(); }
        G2_ISSUE();
        wgmma_commit();
        pos = pos == 4 ? 0 : pos + 1;
        s++;
        fence_async_smem();
        bar_sync(6, 288);
        if (threadIdx.x == 0) TS(49);
        const uint32_t bs0 = ld_nc_u16(P.bsp + row0), bs1 = ld_nc_u16(P.bsp + row0 + 8);
        {
            float sc[2][36];
            G2_ISSUE();
#pragma unroll
            for (int e = 0; e < 2; e++) {
                const uint32_t dq = dlo(sb + QQ_OFF + 4 * e * Q_CH + wg * Q_PAR, Q_CH);
                const uint32_t dk = dlo(sb + KV_OFF + 3 * e * K_CH + wg * K_PAR + 128, K_CH);
                wgmma_n72<0, HI_NOSW, HI_NOSW>(sc[e], dq, dk, false);
                wgmma_n72<0, HI_NOSW, HI_NOSW>(sc[e], dq + (2 * Q_CH >> 4), dk + (2 * K_CH >> 4), true);
            }
            G2_RETIRE();
            G2_ISSUE();
            G2_RETIRE();
            reg_fence(sc[0]); reg_fence(sc[1]);
#define BAND(e, k) (w == 0 ? sc[e][k] : w == 1 ? sc[e][8 + k] : w == 2 ? sc[e][16 + k] : sc[e][24 + k])
            const float NEG = __int_as_float(0xff800000);
            const bool c0 = 2 * t > g, c1 = 2 * t + 1 > g;
            const bool first = (i == 0 && w == 0);
            float l[4][4], mx[4];
#pragma unroll
            for (int e = 0; e < 2; e++) {
                l[2 * e][0] = (c0 && !first) ? BAND(e, 0) : NEG;
                l[2 * e][1] = (c1 && !first) ? BAND(e, 1) : NEG;
                l[2 * e][2] = !c0 ? BAND(e, 4) : NEG;
                l[2 * e][3] = !c1 ? BAND(e, 5) : NEG;
                l[2 * e + 1][0] = c0 ? BAND(e, 6) : NEG;
                l[2 * e + 1][1] = c1 ? BAND(e, 7) : NEG;
                l[2 * e + 1][2] = !c0 ? BAND(e, 10) : NEG;
                l[2 * e + 1][3] = !c1 ? BAND(e, 11) : NEG;
            }
#pragma unroll
            for (int r = 0; r < 4; r++) asm volatile("" : "+f"(l[r][0]), "+f"(l[r][1]), "+f"(l[r][2]), "+f"(l[r][3]));
            G2_ISSUE();
            G2_RETIRE();
#pragma unroll
            for (int r = 0; r < 4; r++) {
                asm volatile("" : "+f"(l[r][0]));
                mx[r] = fmaxf(fmaxf(l[r][0], l[r][1]), fmaxf(l[r][2], l[r][3]));
                mx[r] = fmaxf(mx[r], __shfl_xor_sync(0xffffffffu, mx[r], 1));
                mx[r] = fmaxf(mx[r], __shfl_xor_sync(0xffffffffu, mx[r], 2));
                const float scl = 0.18898223650461362f * 1.4426950408889634f;
                const float off = -mx[r] * scl;
#pragma unroll
                for (int k = 0; k < 4; k++) l[r][k] = ex2(fmaf(l[r][k], scl, off));
                asm volatile("" : "+f"(l[r][0]), "+f"(l[r][1]), "+f"(l[r][2]), "+f"(l[r][3]));
            }
            G2_ISSUE();
            G2_RETIRE();
            uint32_t pp[4][2];
#pragma unroll
            for (int r = 0; r < 4; r++) {
                asm volatile("" : "+f"(l[r][0]));
                const float d = __fdividef(1.0f, quad_sum((l[r][0] + l[r][1]) + (l[r][2] + l[r][3])));
                pp[r][0] = pack_bf16(l[r][0] * d, l[r][1] * d); pp[r][1] = pack_bf16(l[r][2] * d, l[r][3] * d);
                asm volatile("" : "+r"(pp[r][0]), "+r"(pp[r][1]));
            }
            G2_ISSUE();
            G2_RETIRE();
            float oc[2][16];
            uint32_t pf[2][5][4];
#pragma unroll
            for (int e = 0; e < 2; e++)
#pragma unroll
                for (int k = 0; k < 5; k++) {
                    asm volatile("" : "+r"(pp[2 * e][0]));
                    pf[e][k][0] = k == w + 1 ? pp[2 * e][1] : 0u; pf[e][k][1] = k == w + 1 ? pp[2 * e + 1][0] : 0u;
                    pf[e][k][2] = k == w ? pp[2 * e][0] : 0u;     pf[e][k][3] = k == w + 1 ? pp[2 * e + 1][1] : 0u;
                    asm volatile("" : "+r"(pf[e][k][0]), "+r"(pf[e][k][1]), "+r"(pf[e][k][2]), "+r"(pf[e][k][3]));
                }
            G2_ISSUE();
#pragma unroll
            for (int e = 0; e < 2; e++) {
                const uint32_t dv = dlo(sb + KV_OFF + (7 + 3 * e) * K_CH + wg * K_PAR, 128);
#pragma unroll
                for (int k = 0; k < 5; k++) wgmma_rs_n32<1, hi_sbo(K_CH)>(oc[e], pf[e][k][0], pf[e][k][1], pf[e][k][2], pf[e][k][3], dv + k * 16, k != 0);
            }
            G2_RETIRE();
            G2_ISSUE();
            G2_RETIRE();
            reg_fence(oc[0]); reg_fence(oc[1]);
            const int m = lane >> 3;
            const uint32_t oa = sb + OS_OFF + (w >> 1) * 7168 + (m >> 1) * 1024 + ((w & 1) * 32 + (m & 1) * 16 + 2 * (lane & 7) + wg) * 16;
#define OPK(e, k) pack_bf16(oc[e][k], oc[e][k + 1])
            stmat_x4(oa, OPK(0, 0), OPK(0, 2), OPK(0, 4), OPK(0, 6));
            stmat_x4(oa + 2048, OPK(0, 8), OPK(0, 10), t < 2 ? OPK(0, 12) : OPK(1, 0), t < 2 ? OPK(0, 14) : OPK(1, 2));
            stmat_x4(oa + 4096, OPK(1, 4), OPK(1, 6), OPK(1, 8), OPK(1, 10));
            stmat_x2(oa + 6144, OPK(1, 12), OPK(1, 14));
        }
        fence_async_smem();
        bar_arrive(11, 320);
        if (threadIdx.x == 0) TS(46);
        wgmma_wait<0>();
        SIGNAL_DONE(s - 1);
        reg_fence(acc_a);
        {
            const float b0 = bf_lo(bs0), b1 = bf_lo(bs1);
#pragma unroll
            for (int b = 0; b < 14; b++) { acc_a[4 * b] += b0; acc_a[4 * b + 1] += b0; acc_a[4 * b + 2] += b1; acc_a[4 * b + 3] += b1; }
        }
        G2_ISSUE();
        wgmma_commit();
        float z1f[56];
#pragma unroll
        for (int b = 0; b < 28; b++) {
            z1f[2 * b] = bf_lo(z1p[b]); z1f[2 * b + 1] = bf_hi(z1p[b]);
            asm volatile("" : "+f"(z1f[2 * b]), "+f"(z1f[2 * b + 1]));
        }
        wgmma_wait<0>();
        SIGNAL_DONE(s);
        pos = pos == 4 ? 0 : pos + 1;
        s++;
#pragma unroll 1
        while (s < S_C - 1) { G2_ISSUE(); G2_RETIRE0(); }
        G2_ISSUE();
        wgmma_commit();
        if (threadIdx.x == 0) TS(13);
        {
            wait_done(bars, S_C - 2);
            const int m = lane >> 3;
            const uint32_t sa = sb + wg * GRAN + (m >> 1) * 1024 + (w * 16 + (m & 1) * 8 + (lane & 7)) * 16;
            wgmma_wait<0>();
            SIGNAL_DONE(S_C - 1);
            reg_fence(acc_a);
            if (threadIdx.x == 0) TS(8);
#pragma unroll
            for (int b = 0; b < 14; b += 2) {
                stmat_x4(sa + b * 1024,
                         pack_bf16(acc_a[4 * b] * z1f[4 * b], acc_a[4 * b + 1] * z1f[4 * b + 1]),
                         pack_bf16(acc_a[4 * b + 2] * z1f[4 * b + 2], acc_a[4 * b + 3] * z1f[4 * b + 3]),
                         pack_bf16(acc_a[4 * b + 4] * z1f[4 * b + 4], acc_a[4 * b + 5] * z1f[4 * b + 5]),
                         pack_bf16(acc_a[4 * b + 6] * z1f[4 * b + 6], acc_a[4 * b + 7] * z1f[4 * b + 7]));
                if (b == USPLIT - 2) { fence_async_smem(); bar_arrive(7, 288); }
            }
            fence_async_smem();
            bar_arrive(8, 288);
            if (threadIdx.x == 0) TS(9);
            bar_sync(1 + wg, 128);
        }
        float acc3[32];
#pragma unroll
        for (int b = 0; b < 8; b++) {
            acc3[4 * b] = bf_lo(xr[2 * b]); acc3[4 * b + 1] = bf_hi(xr[2 * b]);
            acc3[4 * b + 2] = bf_lo(xr[2 * b + 1]); acc3[4 * b + 3] = bf_hi(xr[2 * b + 1]);
        }
        const uint32_t dA_c = dlo(sb + wg * GRAN, 1024);
        const uint32_t dB_c = dlo(sb, 8192);
        {
            uint32_t q = sb + SEL_OFF;
            int n = 0;
            uint32_t ldone;
            asm volatile("mapa.shared::cluster.u32 %0, %1, %2;" : "=r"(ldone) : "r"(bars + 8 * B_DONE), "r"(h));
#define C_ISSUE() \
                const uint32_t da = dA_c + slot_a_kb(n >> 4) * 64, db = dB_c + slot_w_kb(n >> 4) * 64; \
                q += 4; \
                int nx = __shfl_sync(0xffffffffu, (int)lds_vol(q), 0); \
                wait_full(bars, S_C + (n & 15)); \
                if (threadIdx.x == 0) TS(15 + ((q - sb - SEL_OFF) >> 2)); \
                wgmma_fence(); \
                _Pragma("unroll") \
                for (int k = 0; k < 7; k++) wgmma_n64<1, HI_NOSW, HI_SW128>(acc3, da + k * 128, db + k * 128, true); \
                wgmma_commit();
#define C_NEXT() do { uint32_t cnt = 0; while (nx == 0) { nx = __shfl_sync(0xffffffffu, (int)lds_vol(q), 0); SPIN_CHECK2(cnt, 1700) } n = nx; } while (0)
#pragma unroll 1
            for (int it = 0; it < 7; it++) {
                C_ISSUE();
                wgmma_wait<0>();
                if (sig2) mbar_arrive_cl((it < 5 ? rdone : ldone) + 8 * ((S_C + it) & 15));
                C_NEXT();
            }
#pragma unroll 1
            while (n != 12) {
                C_ISSUE();
                C_NEXT();
            }
        }
        wgmma_wait<0>();
        reg_fence(acc3);
        if (threadIdx.x == 0) TS(10);
        if (j < 7) {
            bf16* op = P.out + (size_t)row0 * 448 + j * 64 + 8 * t;
#pragma unroll
            for (int hf = 0; hf < 4; hf++) {
                const int bb = (hf & 1) * 4, ro = (hf >> 1) * 2;
                uint32_t v0 = pack_bf16(acc3[4 * bb + ro], acc3[4 * bb + ro + 1]), v1 = pack_bf16(acc3[4 * bb + 4 + ro], acc3[4 * bb + 5 + ro]);
                uint32_t v2 = pack_bf16(acc3[4 * bb + 8 + ro], acc3[4 * bb + 9 + ro]), v3 = pack_bf16(acc3[4 * bb + 12 + ro], acc3[4 * bb + 13 + ro]);
                quad_transpose(v0, v1, v2, v3, t);
                *reinterpret_cast<uint4*>(op + bb * 8 + (hf >> 1) * 8 * 448) = make_uint4(v0, v1, v2, v3);
            }
        }
        if (threadIdx.x == 0) TS(11);
    } else {
        asm volatile("setmaxnreg.dec.sync.aligned.u32 72;");
        RELANE();
        bar_sync(9, 384);
        if (threadIdx.x == 256) TS(60);
        if (warp == 8) {
            {
#pragma unroll 1
                for (int n = 0; n < 14; n++) {
                    if (n >= 6) wait_done(bars, n - 6);
                    const uint32_t dst = sb + RINGA_OFF + wslot(n) * 16384;
                    const int col = (n < 7 ? 896 : 0) + j * 112, kb = n < 7 ? n : n - 7;
                    TS2(lane == 0, 32 + n);
                    if (elect_one()) {
                        const uint32_t fb = full_bar(bars, n);
                        mbar_expect_tx(fb, 16384);
                        tma_2d(dst, &P.tm_win, col, kb * 64, fb);
                        tma_2d(dst + 8192, &P.tm_win, col + 64, kb * 64, fb);
                    }
                }
            }
            bar_sync(12, 64);
            fence_async_global();
            cluster_wait();
            {
#define LOAD_WC(n_, sl_) do { \
                    const int u_ = (n_); \
                    const bool iso_ = u_ < 5 && u_ != 2; \
                    if (elect_one()) { \
                        const uint32_t fb_ = full_bar(bars, S_C + u_); \
                        mbar_expect_tx(fb_, (u_ == 2 || ((u_ == 7 || u_ >= 10) && j == 7) ? 0u : 2 * GRAN) + (j < 7 ? GRAN : 0u)); \
                        if (j < 7) tma_2d(sb + slot_w_kb(sl_) * 1024, iso_ ? &P.tm_wo : &P.tm_wout, j * 64, (iso_ ? u_ - (u_ > 2) : tail_src(u_, j)) * 112, fb_); \
                    } \
                } while (0)
                constexpr uint64_t DEP = 0xAA8876653210ull;
                int m = 0, kb = 0, pos = 0;
#pragma unroll 1
                for (int k = 0; k < 39; k++) {
                    wait_done(bars, k < 12 ? 9 + (int)((DEP >> (4 * k)) & 15u) : S_G2 + k - 12);
                    if (k < 8 && k != 6) {
                        TS2(lane == 0, 32 + 14 + m);
                        if (elect_one()) {
                            const uint32_t fb = full_bar(bars, S_J3 + m);
                            mbar_expect_tx(fb, WQ_BYTES);
                            bulk_load(sb + RINGA_OFF + (m & 3) * WQ_BYTES, g_wq + (j * 7 + m) * 1344, WQ_BYTES, fb);
                        }
                        m++;
                    } else {
                        if (kb == 2) mbar_wait(bars + 8 * B_Z2SFREE, 0);
                        TS3(lane == 0, 32 + kb);
                        if (elect_one()) {
                            const uint32_t fb = full_bar(bars, S_G2 + kb);
                            mbar_expect_tx(fb, GBYTES);
                            tma_2d_mc(sb + gstage(pos) + h * 8192, &P.tm_wsp, ((kb + KROT) & 15) * 128 + (kb >> 4) * 64, i * 128 + h * 64, fb);
                        }
                        pos = pos == 4 ? 0 : pos + 1;
                        kb++;

                    }
                }
                mbar_wait(bars + 8 * B_ATTFREE, 0);
                mbar_wait(bars + 8 * B_OREADY, 0);
                fence_async_global();
#pragma unroll 1
                for (int n = 0; n < 12; n++) {
                    wait_done(bars, S_C - 5 + (int)((0xBA9876542210ull >> (4 * n)) & 15u));
                    const int sl = n < 5 ? n : (int)(lds_vol(sb + SEL_OFF + 4 * (n - 5)) >> 4);
                    if (n < 5 && n != 2) {
                        if (lane == 0) TS(33 + n);
                        if (elect_one())
                            bulk_load_mc(sb + slot_a_kb(n) * 1024 + h * GRAN, g_ou + (size_t)(i * 2 + h) * 168 * 1024 + (n - (n > 2)) * GRAN, GRAN, full_bar(bars, S_C + n));
                    }
                    LOAD_WC(n, sl);
                }
            }
        } else if (warp == 9) {
            cluster_wait();
            const unsigned tgt = (ld_relaxed(&g_done) >> 7) + 1u;
            {
                wait_done(bars, 0);
                uint32_t cnt = 0;
                while (!__all_sync(0xffffffffu, ld_relaxed(g_wflag + (j * 32 + min(lane, 27)) * 8) == tgt)) { __nanosleep(100); SPIN_CHECK(cnt, 1400) }
                bar_arrive(12, 64);
                if (lane == 0) {
                    TS(59);
                    asm volatile("prefetch.tensormap [%0];" ::"l"(&P.tm_wsp) : "memory");
                    asm volatile("prefetch.tensormap [%0];" ::"l"(&P.tm_wo) : "memory");
                    asm volatile("prefetch.tensormap [%0];" ::"l"(&P.tm_wout) : "memory");
                }
#pragma unroll 1
                for (int r = 0; r < 16; r++) {
                    if (elect_one()) l2_prefetch(reinterpret_cast<const uint8_t*>(P.wsp) + (size_t)blockIdx.x * 65536 + r * 4096, 4096);
                    __nanosleep(PF_SLEEP);
                }
                if (lane == 0) TS(45);
            }
            {
                unsigned ready = 0, tick = 0;
                int pos = 0;
#pragma unroll 1
                for (int kb = 0; kb < 32; kb++) {
                    wait_done(bars, kb >= 5 ? S_G2 + kb - 5 : 10 + (int)((0x99775u >> (4 * kb)) & 15u));
                    if (kb == 2) mbar_wait(bars + 8 * B_Z2SFREE, 0);
                    uint32_t n = 0;
                    const int f = ((kb + KROT) & 15) | (kb & 16);
                    while ((ready & (ZNEED)) != (ZNEED)) {
                        ready = __ballot_sync(0xffffffffu, ld_relaxed(g_z2flag + (j * 32 + lane) * 8) == tgt);
                        SPIN_CHECK(n, 1100 + kb)
                        fence_async_global();
                    }
                    if (lane == 0 && kb == 0) TS(32);
                    if (kb == 0) tick = __shfl_sync(0xffffffffu, (unsigned)clock(), 0) - PACE0;
                    while ((int)(__shfl_sync(0xffffffffu, (unsigned)clock(), 0) - tick) < 0) {}
                    tick += kb < PK1 ? PACE : kb < PK2 ? PACE2 : PACE3;
                    if (elect_one())
                        bulk_load(sb + gstage(pos) + 16384, g_z2t + (size_t)((f & 15) * 8 + j) * 28672 + (kb >> 4) * GRAN, GRAN, full_bar(bars, S_G2 + kb));
                    pos = pos == 4 ? 0 : pos + 1;
                }
            }
            {
                const bool other = lane == 4 || lane >= 12;
                const int n = lane == 4 ? 7 : lane >= 12 ? min(lane - 2, 11) : lane;
                const bool local = n == 7 || n >= 10;
                const int hh = other ? h ^ 1 : h;
                const int jt = tail_src(n, j);
                const int dep = S_C - 5 + n;
                const uint32_t dbar = done_bar(bars, dep), dpar = (dep >> 4) & 1;
                const uint32_t xbar = bars + 8 * (n == 7 ? B_USTFREE : B_FULLX);
                const uint8_t* sp = g_ou + (size_t)(i * 2 + hh) * 168 * 1024 + (size_t)(4 + jt) * GRAN;
                const uint32_t fb = full_bar(bars, S_C + n);
                bool pending = lane >= 4 && lane < 14 && (j < 7 || !local);
                const uint32_t need = 1u << (jt + (other ? 8 : 0));
                uint32_t cnt = 0;
                while (__any_sync(0xffffffffu, pending)) {
                    const bool go = pending && (lds_vol(sb + UFLAG_OFF) & need) && mbar_test(dbar, dpar) && mbar_test(xbar, 0);
                    if (go) {
                        TS(33 + n);
                        const uint32_t dst = sb + slot_a_kb(lds_vol(sb + SEL_OFF + 4 * (n - 5)) >> 4) * 1024 + hh * GRAN;
                        if (local) bulk_load(dst, sp, GRAN, fb); else bulk_load_mc(dst, sp, GRAN, fb);
                        pending = false;
                    }
                    SPIN_CHECK2(cnt, 1200)
                }
            }
        } else {
            const int a = warp - 10;
            const int hb = i * 2 + a;
            const unsigned tgt = (ld_relaxed(&g_done) >> 7) + 1u;
            if (lane == 0) {
                if (a == 0) l2_prefetch(reinterpret_cast<const uint8_t*>(P.wqkv) + (size_t)blockIdx.x * 9408, 9408);
                else l2_prefetch(reinterpret_cast<const uint8_t*>(P.win) + (size_t)blockIdx.x * 12544, 12544);
            }
            if (lane < 2) {
                const uint4 z = make_uint4(0u, 0u, 0u, 0u);
                st_relaxed_v4(reinterpret_cast<uint4*>(g_wflag + (j * 32 + hb) * 8) + lane, z);
                if (a == 0) {
                    st_relaxed_v4(reinterpret_cast<uint4*>(g_z2flag + (j * 32 + i) * 8) + lane, z);
                    st_relaxed_v4(reinterpret_cast<uint4*>(g_ouflag + (i * 32 + j) * 8) + lane, z);
                    st_relaxed_v4(reinterpret_cast<uint4*>(g_ouflag + (i * 32 + 16 + j) * 8) + lane, z);
                    st_relaxed_v4(reinterpret_cast<uint4*>(g_z2flag + (j * 32 + 16 + i) * 8) + lane, z);
                }
                st_relaxed_v4(reinterpret_cast<uint4*>(g_ouflag + (hb * 16 + 8 + j) * 8) + lane, z);
            }
            const uint32_t rb = bars + 8 * (B_OREADY + 1 + a);
            mbar_wait(bars + 8 * (B_FULLX + 1), 0);
            if (hb < 28) {
                const uint32_t stg = sb + Z2S_OFF + a * 5376;
                if (lane == 0) {
                    mbar_expect_tx(rb, 5376);
#pragma unroll 1
                    for (int q = 0; q < 3; q++) tma_3d(stg + q * 1792, &P.tm_wqkv, 0, hb * 16, q * 56 + j * 7, rb);
                }
                __syncwarp();
                mbar_wait(rb, 0);
                if (lane == 0) {
                    bulk_store(g_wq + (j * 28 + hb) * 336, stg, 5376);
                    asm volatile("cp.async.bulk.wait_group 0;" ::: "memory");
                    PUBLISH(g_wflag + (j * 32 + hb) * 8, tgt);
                    if (a == 0) TS(61);
                }
            }
            if (lane == 0) {
                if (a == 0) l2_prefetch(reinterpret_cast<const uint8_t*>(P.wo) + (size_t)blockIdx.x * 3136, 3136);
                else l2_prefetch(reinterpret_cast<const uint8_t*>(P.wout) + (size_t)blockIdx.x * 6272, 6272);
            }
            __syncwarp();
            cluster_wait();
            {
                const uint32_t tag = (tgt % 3u) + 1u;
                const uint4* sp = g_stats + (i * 8 * 64 + a * 32 + lane);
                wait_done(bars, S_J2 + 1);
                float S0, Q0, S1, Q1;
                uint32_t n = 0;
                while (true) {
                    uint4 p[8];
#pragma unroll
                    for (int c = 0; c < 8; c++) p[c] = ld_relaxed_v4(sp + c * 64);
                    uint32_t all = 3u, any = 0u;
                    S0 = Q0 = S1 = Q1 = 0.f;
#pragma unroll
                    for (int c = 0; c < 8; c++) {
                        all &= p[c].x & p[c].y & p[c].z & p[c].w; any |= p[c].x | p[c].y | p[c].z | p[c].w;
                        S0 += __uint_as_float(p[c].x); Q0 += __uint_as_float(p[c].y); S1 += __uint_as_float(p[c].z); Q1 += __uint_as_float(p[c].w);
                    }
                    if (__all_sync(0xffffffffu, all == tag && (any & 3u) == tag)) break;
                    SPIN_CHECK(n, 1000)
                }
                const float m0 = S0 * (1.0f / 896.0f), m1 = S1 * (1.0f / 896.0f);
                const float r0 = rsqrtf(fmaxf(Q0 * (1.0f / 896.0f) - m0 * m0, 0.f) + 1e-5f);
                const float r1 = rsqrtf(fmaxf(Q1 * (1.0f / 896.0f) - m1 * m1, 0.f) + 1e-5f);
                sts_v4(sb + STAT_OFF + (a * 32 + lane) * 16, make_uint4(__float_as_uint(r0), __float_as_uint(-m0 * r0), __float_as_uint(r1), __float_as_uint(-m1 * r1)));
                __syncwarp();
                if (lane == 0) mbar_arrive(bars + 8 * (B_STATS + a));
            }
            if (a == 0) {
                uint8_t* dst = g_z2t + (size_t)(i * 8 + j) * 28672;
                bar_sync(3, 160);
                if (lane == 0) {
                    bulk_store(dst, sb + Z2S_OFF, 7168);
                    asm volatile("cp.async.bulk.wait_group.read 0;" ::: "memory");
                    bulk_store(dst + 7168, sb + Z2S_OFF + 7168, 7168);
                    asm volatile("cp.async.bulk.wait_group.read 0;" ::: "memory");
                }
                __syncwarp();
                bar_sync(4, 160);
                if (lane == 0) {
                    bulk_store(dst + GRAN, sb + Z2S_OFF + GRAN, 7168);
                    asm volatile("cp.async.bulk.wait_group 1;" ::: "memory");
                    PUBLISH(g_z2flag + (j * 32 + i) * 8, tgt);
                    TS(47);
                    asm volatile("cp.async.bulk.wait_group.read 0;" ::: "memory");
                    bulk_store(dst + GRAN + 7168, sb + Z2S_OFF + GRAN + 7168, 7168);
                    asm volatile("cp.async.bulk.wait_group 0;" ::: "memory");
                    PUBLISH(g_z2flag + (j * 32 + 16 + i) * 8, tgt);
                    mbar_arrive(bars + 8 * B_Z2SFREE);
                    mbar_arrive_remote(bars + 8 * B_Z2SFREE, h ^ 1);
                    TS(48);
                }
                __syncwarp();
            }
            if (a == 0) {
                wait_done(bars, S_G2);
                uint4 hv[14];
                if (i > 0) {
                    const uint4* hp = g_halo + (size_t)(((i - 1) * 8 + j) * 14) * 32 + lane;
                    uint32_t n = 0;
                    while (true) {
                        bool ok = true;
#pragma unroll
                        for (int c = 0; c < 14; c++) hv[c] = ld_relaxed_v4(hp + c * 32);
#pragma unroll
                        for (int c = 0; c < 14; c++) ok = ok && hv[c].y == tgt && hv[c].w == tgt;
                        if (__all_sync(0xffffffffu, ok)) break;
                        POLL_SLEEP;
                        SPIN_CHECK(n, 1300)
                    }
                } else {
#pragma unroll
                    for (int c = 0; c < 14; c++) hv[c] = make_uint4(0u, 0u, 0u, 0u);
                }
                const int m = lane >> 3;
                const int r = (m & 1) * 8 + (lane & 7);
                const uint32_t sa = sb + KV_OFF + (m >> 1) * K_CH + (r & 1) * K_PAR + (r >> 1) * 16;
#pragma unroll
                for (int c = 0; c < 14; c += 2) {
                    stmat_x4(sa + c * K_CH + 128, hv[c].x, hv[c].z, hv[c + 1].x, hv[c + 1].z);
                    if (c >= 6) stmat_x4(sa + c * K_CH, 0u, 0u, 0u, 0u);
                }
                fence_async_smem();
                bar_arrive(6, 288);
                if (lane == 0) TS(50);
            }
            bar_sync(11, 320);
            if (lane == 0) {
                bulk_store(g_ou + ((size_t)hb * 168 + 7 * j) * 1024, sb + OS_OFF + a * 7168, 7168);
                asm volatile("cp.async.bulk.wait_group 0;" ::: "memory");
                PUBLISH(g_ouflag + (hb * 16 + 8 + j) * 8, tgt);
                mbar_arrive(bars + 8 * B_ATTFREE);
                if (a == 0) TS(51);
            }
            __syncwarp();
            if (a == 1) {
                uint32_t cnt = 0;
                while (!__all_sync(0xffffffffu, ld_relaxed(g_ouflag + ((i * 2 + h) * 16 + 8 + (lane & 7)) * 8) == tgt)) { POLL_SLEEP; SPIN_CHECK(cnt, 1500) }
                fence_async_global();
                if (lane == 0) { mbar_arrive(bars + 8 * B_OREADY); TS(62); }
                __syncwarp();
            }
            if (a == 0) {
                uint8_t* dst = g_ou + ((size_t)i * 2 * 168 + 56 + 14 * j) * 1024;
                bar_sync(7, 288);
                if (lane == 0) {
                    bulk_store(dst, sb, USPLIT * 1024);
                    bulk_store(dst + 168 * 1024, sb + GRAN, USPLIT * 1024);
                }
                __syncwarp();
                bar_sync(8, 288);
                if (lane == 0) {
                    bulk_store(dst + USPLIT * 1024, sb + USPLIT * 1024, GRAN - USPLIT * 1024);
                    bulk_store(dst + (168 + USPLIT) * 1024, sb + GRAN + USPLIT * 1024, GRAN - USPLIT * 1024);
                    asm volatile("cp.async.bulk.wait_group 1;" ::: "memory");
                    PUBLISH(UFLAG(i * 2, j), tgt);
                    asm volatile("cp.async.bulk.wait_group 0;" ::: "memory");
                    PUBLISH(UFLAG(i * 2 + 1, j), tgt);
                    mbar_arrive(bars + 8 * B_USTFREE);
                    mbar_arrive_remote(bars + 8 * B_USTFREE, h ^ 1);
                    atomicAdd(&g_done, 1u);
                    TS(52);
                }
                __syncwarp();
                bool pending = lane >= 5 && lane < 12;
                const uint32_t mybar = full_bar(bars, S_C + lane), mypar = ((S_C + lane) >> 4) & 1;
                uint32_t q = sb + SEL_OFF + 20, cnt = 0;
                while (q != sb + SEL_OFF + 48) {
                    const bool go = pending && mbar_test(mybar, mypar);
                    const uint32_t rdy = __ballot_sync(0xffffffffu, go);
                    if (go) { sts_vol(q + 4 * __popc(rdy & ((1u << lane) - 1u)), (uint32_t)lane | (lds_vol(sb + SEL_OFF + 4 * (lane - 5)) & 0xf0u)); pending = false; }
                    q += 4 * __popc(rdy);
                    SPIN_CHECK2(cnt, 1900)
                }
            } else {
                wait_done(bars, S_C - 3);
                const unsigned* fp = UFLAG(i * 2 + (h ^ ((lane >> 3) & 1)), lane & 7);
                uint32_t cnt = 0, mask = ~((0xffu & ~(1u << j)) | (0x100u << (j ^ 1)) | (0x100u << tail_src(10, j)) | (0x100u << tail_src(11, j)));
                while (mask != 0xffffffffu) {
                    unsigned v = 0;
                    if (!((mask >> lane) & 1u)) v = ld_relaxed(fp);
                    mask |= __ballot_sync(0xffffffffu, v == tgt);
                    AUX_FENCE;
                    if (lane == 0) sts_vol(sb + UFLAG_OFF, mask);
                    SPIN_CHECK(cnt, 1600)
                }
                if (lane == 0) { TS(30); }
            }
        }
    }
}

typedef CUresult (*PFN_encodeTiled)(CUtensorMap*, CUtensorMapDataType, cuuint32_t, void*, const cuuint64_t*, const cuuint64_t*,
                                    const cuuint32_t*, const cuuint32_t*, CUtensorMapInterleave, CUtensorMapSwizzle,
                                    CUtensorMapL2promotion, CUtensorMapFloatOOBfill);

void make_map(PFN_encodeTiled enc, CUtensorMap* tm, const void* ptr, int rank, const cuuint64_t* dims, const cuuint64_t* strides,
              const cuuint32_t* box, CUtensorMapSwizzle sw) {
    cuuint32_t es[3] = {1, 1, 1};
    enc(tm, CU_TENSOR_MAP_DATA_TYPE_BFLOAT16, rank, const_cast<void*>(ptr), dims, strides, box, es, CU_TENSOR_MAP_INTERLEAVE_NONE,
        sw, L2PROMO, CU_TENSOR_MAP_FLOAT_OOB_FILL_NONE);
}

}

extern "C" void kernel_launch(void* const* d_in, const int* in_sizes, int n_in, void* d_out, int out_size) {
    (void)in_sizes; (void)n_in; (void)out_size;
    PFN_encodeTiled enc = nullptr;
    cudaDriverEntryPointQueryResult st;
    cudaGetDriverEntryPoint("cuTensorMapEncodeTiled", (void**)&enc, cudaEnableDefault, &st);
    Params P;
    P.x = (const bf16*)d_in[0];
    P.wqkv = (const bf16*)d_in[1];
    P.wo = (const bf16*)d_in[2];
    P.win = (const bf16*)d_in[4];
    P.wsp = (const bf16*)d_in[5];
    P.bsp = (const bf16*)d_in[6];
    P.wout = (const bf16*)d_in[7];
    P.out = (bf16*)d_out;
    {
        cuuint64_t d[2] = {1792, 448}, s[1] = {3584}; cuuint32_t b[2] = {64, 64};
        make_map(enc, &P.tm_win, P.win, 2, d, s, b, CU_TENSOR_MAP_SWIZZLE_128B);
    }
    {
        cuuint64_t d[2] = {448, 2048}, s[1] = {896}; cuuint32_t b[2] = {64, 64};
        make_map(enc, &P.tm_x, P.x, 2, d, s, b, CU_TENSOR_MAP_SWIZZLE_128B);
    }
    {
        cuuint64_t d[2] = {2048, 2048}, s[1] = {4096}; cuuint32_t b[2] = {64, 64};
        make_map(enc, &P.tm_wsp, P.wsp, 2, d, s, b, CU_TENSOR_MAP_SWIZZLE_128B);
    }
    {
        cuuint32_t b[3] = {8, 16, 7};
        cuuint64_t d0[3] = {8, 448, 168}, s0[2] = {2688, 16};
        make_map(enc, &P.tm_wqkv, P.wqkv, 3, d0, s0, b, CU_TENSOR_MAP_SWIZZLE_NONE);
        cuuint32_t bw[2] = {64, 112};
        cuuint64_t d1[2] = {448, 448}, s1[1] = {896};
        make_map(enc, &P.tm_wo, P.wo, 2, d1, s1, bw, CU_TENSOR_MAP_SWIZZLE_128B);
        cuuint64_t d2[2] = {448, 896};
        make_map(enc, &P.tm_wout, P.wout, 2, d2, s1, bw, CU_TENSOR_MAP_SWIZZLE_128B);
    }
    cudaFuncSetAttribute(fused_kernel, cudaFuncAttributeMaxDynamicSharedMemorySize, SMEM_BYTES);
    fused_kernel<<<128, 384, SMEM_BYTES>>>(P);
}
```
